```python
import torch

def _softmax(x, axis=-1):
    return torch.softmax(x, dim=axis)
def _gelu(x):
    return torch.nn.functional.gelu(x, approximate="tanh")
def _silu(x):
    return torch.nn.functional.silu(x)
def _sigmoid(x):
    return torch.sigmoid(x)
def _layernorm(x, axis=-1, eps=1e-5):
    m = x.mean(dim=axis, keepdim=True)
    v = x.var(dim=axis, keepdim=True, unbiased=False)
    return (x - m) / torch.sqrt(v + eps)
def _scatter_add(tgt, idx, src, axis=0):
    return tgt.clone().index_add_(axis, idx, src)
def _segment_sum(src, seg, n):
    out = torch.zeros((n,) + src.shape[1:], dtype=src.dtype)
    return out.index_add_(0, seg, src)
def _pad(x, pw):
    flat = tuple(v for pair in reversed(pw) for v in pair)
    return torch.nn.functional.pad(x, flat)

kernel_name = 'concat_heads__mha_block_cached__gqa_block_cached__near_ridge'

def setup_inputs():

    _w = (lambda a: (lambda t: t.to(torch.bfloat16) if t.is_floating_point() else t)(torch.as_tensor(a)))
    def _A_setup():
        B, Sq, D = 8, 144, 1024
        H, Sk, Dh = 32, 512, 128
        return {
            "x": _w((lambda *s: torch.randn(*s, dtype=torch.bfloat16) * 0.8)(B, Sq, D)),
            "k_cache": _w((lambda *s: torch.randn(*s, dtype=torch.bfloat16) * 0.8)(B, H, Sk, Dh)),
            "v_cache": _w((lambda *s: torch.randn(*s, dtype=torch.bfloat16) * 0.05)(B, H, Sk, Dh)),
            "wq": _w((lambda *s: torch.randn(*s, dtype=torch.bfloat16) * 0.8)(D, H * Dh) * (D ** -0.5)),
            "wo": _w((lambda *s: torch.randn(*s, dtype=torch.bfloat16) * 0.05)(H * Dh, D) * ((H * Dh) ** -0.5)),
        }
    _A_in = _A_setup()

    def _B_setup():
        B, Sq, D = 8, 144, 1024
        Hq, Hkv, Sk, Dh = 32, 32, 512, 128
        assert Hq % Hkv == 0, (Hq, Hkv)
        return {
            "x": _w((lambda *s: torch.randn(*s, dtype=torch.bfloat16) * 0.8)(B, Sq, D)),
            "k_cache": _w((lambda *s: torch.randn(*s, dtype=torch.bfloat16) * 0.8)(B, Hkv, Sk, Dh)),
            "v_cache": _w((lambda *s: torch.randn(*s, dtype=torch.bfloat16) * 0.05)(B, Hkv, Sk, Dh)),
            "wq": _w((lambda *s: torch.randn(*s, dtype=torch.bfloat16) * 0.8)(D, Hq * Dh) * (D ** -0.5)),
            "wo": _w((lambda *s: torch.randn(*s, dtype=torch.bfloat16) * 0.05)(Hq * Dh, D) * ((Hq * Dh) ** -0.5)),
        }
    _B_in = _B_setup()

    return {
        "A_x": _A_in["x"],
        "A_k_cache": _A_in["k_cache"],
        "A_v_cache": _A_in["v_cache"],
        "A_wq": _A_in["wq"],
        "A_wo": _A_in["wo"],
        "B_x": _B_in["x"],
        "B_k_cache": _B_in["k_cache"],
        "B_v_cache": _B_in["v_cache"],
        "B_wq": _B_in["wq"],
        "B_wo": _B_in["wo"],
    }

def reference(A_x, A_k_cache, A_v_cache, A_wq, A_wo, B_x, B_k_cache, B_v_cache, B_wq, B_wo):
    def _A_ref(x, k_cache, v_cache, wq, wo):
        B, Sq, D = x.shape
        H, Dh = 32, 128
        q = (lambda x, *d: x.permute(*d))((x @ wq).reshape(B, Sq, H, Dh), 0, 2, 1, 3)
        scores = torch.einsum("bhqd,bhkd->bhqk", q, k_cache) * (Dh ** -0.5)
        p = _softmax(scores, axis=-1)
        o = torch.einsum("bhqk,bhkd->bhqd", p, v_cache)
        return (lambda x, *d: x.permute(*d))(o, 0, 2, 1, 3).reshape(B, Sq, H * Dh) @ wo

    def _B_ref(x, k_cache, v_cache, wq, wo):
        B, Sq, D = x.shape
        Hq, Dh = 32, 128
        Hkv = k_cache.shape[1]
        rep = Hq // Hkv
        q = (lambda x, *d: x.permute(*d))((x @ wq).reshape(B, Sq, Hq, Dh), 0, 2, 1, 3)
        k = (lambda x, n, axis: torch.repeat_interleave(x, n, dim=axis))(k_cache, rep, axis=1)
        v = (lambda x, n, axis: torch.repeat_interleave(x, n, dim=axis))(v_cache, rep, axis=1)
        scores = torch.einsum("bhqd,bhkd->bhqk", q, k) * (Dh ** -0.5)
        p = _softmax(scores, axis=-1)
        o = torch.einsum("bhqk,bhkd->bhqd", p, v)
        return (lambda x, *d: x.permute(*d))(o, 0, 2, 1, 3).reshape(B, Sq, Hq * Dh) @ wo

    a = _A_ref(A_x, A_k_cache, A_v_cache, A_wq, A_wo)
    b = _B_ref(B_x, B_k_cache, B_v_cache, B_wq, B_wo)
    return torch.concatenate([a, b], axis=-1)
```

```cpp
#include <cuda_runtime.h>
#include <cuda.h>
#include <cuda_bf16.h>
#include <stdint.h>

namespace {

constexpr int SQ = 144;
constexpr int TOK = 1152;
constexpr int SLOT = 18432;
constexpr int NSLOT = 12;
constexpr int PAIR = 2 * SLOT;
constexpr int OFF_BAR = NSLOT * SLOT;
constexpr int OFF_MAX = OFF_BAR + 256;
constexpr int OFF_SUM = OFF_MAX + 2 * 576;
constexpr int OFF_INV = OFF_SUM + 8 * 288;
constexpr int OFF_TR = OFF_INV + 576;
constexpr int SMEM_BYTES = OFF_TR + 1024 + 2560 + 1024;
constexpr int NCTA = 128;
#define PF_LEAD 4

struct alignas(64) Params {
  CUtensorMap x[2], wq[2], k[2], v[2], wo[2], os, out;
  const char* kptr[2];
  const char* vptr[2];
  const char* xptr[2];
  const char* wqptr[2];
  const char* woptr[2];
  uint32_t zero;
};

__device__ __nv_bfloat16 g_oscr[2 * TOK * 4096];
__device__ uint4 g_park[NCTA * 4 * (PAIR / 16)];
__device__ unsigned int g_cnt[64];
__device__ unsigned int g_done;

#define TR(idx)
#define TRG(i)
#define TRDUMP()
#define TRS(i)
#define TRSDUMP()
#define TRINIT()
__device__ __forceinline__ uint32_t smem_u32(const void* p) { return (uint32_t)__cvta_generic_to_shared(p); }
__device__ __forceinline__ void mbar_init(uint32_t bar, int cnt) {
  asm volatile("mbarrier.init.shared::cta.b64 [%0], %1;" :: "r"(bar), "r"(cnt));
}
__device__ __forceinline__ void mbar_arrive(uint32_t bar) {
  asm volatile("mbarrier.arrive.shared::cta.b64 _, [%0];" :: "r"(bar) : "memory");
}
__device__ __forceinline__ void mbar_arrive_cta(uint32_t bar, uint32_t cta, uint32_t cnt) {
  asm volatile("{\n.reg .b32 ra;\nmapa.shared::cluster.u32 ra, %0, %1;\n"
               "mbarrier.arrive.shared::cluster.b64 _, [ra], %2;\n}\n" :: "r"(bar), "r"(cta), "r"(cnt) : "memory");
}
__device__ __forceinline__ void mbar_wait(uint32_t bar, uint32_t parity) {
  asm volatile("{\n.reg .pred p;\n.reg .u32 c;\nmov.u32 c, 0;\n"
    "LAB_WAIT:\n"
    "mbarrier.try_wait.parity.shared::cta.b64 p, [%0], %1;\n"
    "@p bra DONE;\n"
    "add.u32 c, c, 1;\n"
    "setp.lt.u32 p, c, 400000;\n"
    "@p bra LAB_WAIT;\n"
    "DONE:\n}\n" :: "r"(bar), "r"(parity) : "memory");
}
#define ELECT_BEGIN "{\n.reg .pred p;\nelect.sync _|p, 0xffffffff;\n"
__device__ __forceinline__ void tma2d(uint32_t dst, const CUtensorMap* map, int c0, int c1, uint32_t bar, uint32_t bytes) {
  asm volatile(ELECT_BEGIN "@p mbarrier.arrive.expect_tx.shared::cta.b64 _, [%2], %5;\n"
    "@p cp.async.bulk.tensor.2d.shared::cluster.global.mbarrier::complete_tx::bytes [%0], [%1, {%3, %4}], [%2];\n}\n"
    :: "r"(dst), "l"(map), "r"(bar), "r"(c0), "r"(c1), "r"(bytes) : "memory");
}
__device__ __forceinline__ void tma2d_mc(uint32_t dst, const CUtensorMap* map, int c0, int c1, uint32_t bar) {
  asm volatile(ELECT_BEGIN
    "@p cp.async.bulk.tensor.2d.shared::cluster.global.mbarrier::complete_tx::bytes.multicast::cluster [%0], [%1, {%3, %4}], [%2], %5;\n}\n"
    :: "r"(dst), "l"(map), "r"(bar), "r"(c0), "r"(c1), "h"((uint16_t)3) : "memory");
}
__device__ __forceinline__ void tma3d_hint(uint32_t dst, const CUtensorMap* map, int c1, uint32_t bar, uint64_t pol, uint32_t bytes) {
  asm volatile(ELECT_BEGIN "@p mbarrier.arrive.expect_tx.shared::cta.b64 _, [%2], %6;\n"
    "@p cp.async.bulk.tensor.3d.shared::cluster.global.mbarrier::complete_tx::bytes.L2::cache_hint [%0], [%1, {%3, %4, %3}], [%2], %5;\n}\n"
    :: "r"(dst), "l"(map), "r"(bar), "r"(0), "r"(c1), "l"(pol), "r"(bytes) : "memory");
}
__device__ __forceinline__ void tma2d_store(const CUtensorMap* map, int c0, int c1, uint32_t src) {
  asm volatile("cp.async.bulk.tensor.2d.global.shared::cta.bulk_group [%0, {%1, %2}], [%3];"
    :: "l"(map), "r"(c0), "r"(c1), "r"(src) : "memory");
}
__device__ __forceinline__ void sched_sep(uint32_t zero) {
  asm volatile("{\n.reg .pred p;\n.reg .u32 c;\nSEP_L:\n.pragma \"nounroll\";\nmov.u32 c, %%clock;\nsetp.lt.u32 p, c, %0;\n@p bra SEP_L;\n}\n" :: "r"(zero) : "memory");
}
__device__ __forceinline__ void wg_fence() { asm volatile("wgmma.fence.sync.aligned;" ::: "memory"); }
__device__ __forceinline__ void wg_commit() { asm volatile("wgmma.commit_group.sync.aligned;" ::: "memory"); }
template<int N> __device__ __forceinline__ void wg_wait() { asm volatile("wgmma.wait_group.sync.aligned %0;" :: "n"(N) : "memory"); }
__device__ __forceinline__ void fence_regs(float (&d)[72]) {
  #pragma unroll
  for (int i = 0; i < 72; i++) asm volatile("" : "+f"(d[i]) :: "memory");
}
__device__ __forceinline__ void fence_async_smem() { asm volatile("fence.proxy.async.shared::cta;" ::: "memory"); }
template<int ID, int N> __device__ __forceinline__ void bar_sync() { asm volatile("bar.sync %0, %1;" :: "n"(ID), "n"(N) : "memory"); }
__device__ __forceinline__ void cluster_sync() {
  asm volatile("barrier.cluster.arrive.release.aligned;\nbarrier.cluster.wait.acquire.aligned;" ::: "memory");
}
__device__ __forceinline__ uint32_t pack_bf16(float lo, float hi) {
  uint32_t r; asm("cvt.rn.bf16x2.f32 %0, %1, %2;" : "=r"(r) : "f"(hi), "f"(lo)); return r;
}
__device__ __forceinline__ uint32_t max_bf16x2(uint32_t a, uint32_t b) {
  uint32_t r; asm("max.bf16x2 %0, %1, %2;" : "=r"(r) : "r"(a), "r"(b)); return r;
}
__device__ __forceinline__ uint32_t add_bf16x2(uint32_t a, uint32_t b) {
  uint32_t r; asm("add.rn.bf16x2 %0, %1, %2;" : "=r"(r) : "r"(a), "r"(b)); return r;
}
__device__ __forceinline__ uint32_t sub_bf16x2(uint32_t a, uint32_t b) {
  uint32_t r; asm("sub.rn.bf16x2 %0, %1, %2;" : "=r"(r) : "r"(a), "r"(b)); return r;
}
__device__ __forceinline__ uint32_t ex2_bf16x2(uint32_t a) {
  uint32_t r;
  asm("{\n.reg .b32 t;\nex2.approx.ftz.bf16x2 t, %1;\nmax.NaN.bf16x2 %0, t, %2;\n}\n" : "=r"(r) : "r"(a), "r"(0u));
  return r;
}
__device__ __forceinline__ uint32_t ex2_bf16x2_raw(uint32_t a) {
  uint32_t r; asm("ex2.approx.ftz.bf16x2 %0, %1;" : "=r"(r) : "r"(a)); return r;
}
__device__ __forceinline__ void ldsm4t(uint32_t addr, uint32_t& a, uint32_t& b, uint32_t& c, uint32_t& d) {
  asm volatile("ldmatrix.sync.aligned.m8n8.x4.trans.shared.b16 {%0, %1, %2, %3}, [%4];"
    : "=r"(a), "=r"(b), "=r"(c), "=r"(d) : "r"(addr));
}
__device__ __forceinline__ float bf_lo(uint32_t v) { return __uint_as_float(v << 16); }
__device__ __forceinline__ float bf_hi(uint32_t v) { return __uint_as_float(v & 0xffff0000u); }
__device__ __forceinline__ void stsm4t(uint32_t addr, uint32_t a, uint32_t b, uint32_t c, uint32_t d) {
  asm volatile("stmatrix.sync.aligned.m8n8.x4.trans.shared.b16 [%0], {%1, %2, %3, %4};"
    :: "r"(addr), "r"(a), "r"(b), "r"(c), "r"(d));
}
__device__ __forceinline__ float4 lds128(uint32_t addr) {
  float4 v; asm volatile("ld.shared.v4.f32 {%0, %1, %2, %3}, [%4];" : "=f"(v.x), "=f"(v.y), "=f"(v.z), "=f"(v.w) : "r"(addr)); return v;
}
__device__ __forceinline__ void red_max_f32(uint32_t addr, float v, bool on) {
  asm volatile("{\n.reg .pred p, q, e;\nsetp.ne.b32 e, %2, 0;\nsetp.ge.and.s32 p|q, %1, 0, e;\n"
               "@p red.shared.max.s32 [%0], %1;\n@q red.shared.min.u32 [%0], %1;\n}\n"
               :: "r"(addr), "r"(__float_as_uint(v)), "r"((uint32_t)on) : "memory");
}
template<int ID, int N> __device__ __forceinline__ void bar_arrive() { asm volatile("bar.arrive %0, %1;" :: "n"(ID), "n"(N) : "memory"); }

template<int TA, int OA, int OB>
__device__ __forceinline__ void mma(float (&d)[72], uint32_t a, uint32_t b) {
  asm volatile("{\n.reg .b64 da, db;\n.reg .b32 ta, tb, th;\n"
    "add.u32 ta, %72, %75;\nadd.u32 tb, %73, %76;\nmov.b32 th, 0x40000040;\n"
    "mov.b64 da, {ta, th};\nmov.b64 db, {tb, th};\n"
    "wgmma.mma_async.sync.aligned.m64n144k16.f32.bf16.bf16 "
    "{%0, %1, %2, %3, %4, %5, %6, %7, %8, %9, %10, %11, %12, %13, %14, %15, %16, %17, %18, %19, %20, %21, %22, %23, %24, %25, %26, %27, %28, %29, %30, %31, %32, %33, %34, %35, %36, %37, %38, %39, %40, %41, %42, %43, %44, %45, %46, %47, %48, %49, %50, %51, %52, %53, %54, %55, %56, %57, %58, %59, %60, %61, %62, %63, %64, %65, %66, %67, %68, %69, %70, %71}, "
    "da, db, 1, 1, 1, %74, 0;\n}\n"
    : "+f"(d[0]), "+f"(d[1]), "+f"(d[2]), "+f"(d[3]), "+f"(d[4]), "+f"(d[5]), "+f"(d[6]), "+f"(d[7]), "+f"(d[8]), "+f"(d[9]), "+f"(d[10]), "+f"(d[11]), "+f"(d[12]), "+f"(d[13]), "+f"(d[14]), "+f"(d[15]), "+f"(d[16]), "+f"(d[17]), "+f"(d[18]), "+f"(d[19]), "+f"(d[20]), "+f"(d[21]), "+f"(d[22]), "+f"(d[23]), "+f"(d[24]), "+f"(d[25]), "+f"(d[26]), "+f"(d[27]), "+f"(d[28]), "+f"(d[29]), "+f"(d[30]), "+f"(d[31]), "+f"(d[32]), "+f"(d[33]), "+f"(d[34]), "+f"(d[35]), "+f"(d[36]), "+f"(d[37]), "+f"(d[38]), "+f"(d[39]), "+f"(d[40]), "+f"(d[41]), "+f"(d[42]), "+f"(d[43]), "+f"(d[44]), "+f"(d[45]), "+f"(d[46]), "+f"(d[47]), "+f"(d[48]), "+f"(d[49]), "+f"(d[50]), "+f"(d[51]), "+f"(d[52]), "+f"(d[53]), "+f"(d[54]), "+f"(d[55]), "+f"(d[56]), "+f"(d[57]), "+f"(d[58]), "+f"(d[59]), "+f"(d[60]), "+f"(d[61]), "+f"(d[62]), "+f"(d[63]), "+f"(d[64]), "+f"(d[65]), "+f"(d[66]), "+f"(d[67]), "+f"(d[68]), "+f"(d[69]), "+f"(d[70]), "+f"(d[71])
    : "r"(a), "r"(b), "n"(TA), "n"(OA / 16), "n"(OB / 16));
}

template<int TA, int OA, int OB>
__device__ __forceinline__ void mma_init(float (&d)[72], uint32_t a, uint32_t b) {
  asm volatile("{\n.reg .b64 da, db;\n.reg .b32 ta, tb, th;\n"
    "add.u32 ta, %72, %75;\nadd.u32 tb, %73, %76;\nmov.b32 th, 0x40000040;\n"
    "mov.b64 da, {ta, th};\nmov.b64 db, {tb, th};\n"
    "wgmma.mma_async.sync.aligned.m64n144k16.f32.bf16.bf16 "
    "{%0, %1, %2, %3, %4, %5, %6, %7, %8, %9, %10, %11, %12, %13, %14, %15, %16, %17, %18, %19, %20, %21, %22, %23, %24, %25, %26, %27, %28, %29, %30, %31, %32, %33, %34, %35, %36, %37, %38, %39, %40, %41, %42, %43, %44, %45, %46, %47, %48, %49, %50, %51, %52, %53, %54, %55, %56, %57, %58, %59, %60, %61, %62, %63, %64, %65, %66, %67, %68, %69, %70, %71}, "
    "da, db, 0, 1, 1, %74, 0;\n}\n"
    : "=f"(d[0]), "=f"(d[1]), "=f"(d[2]), "=f"(d[3]), "=f"(d[4]), "=f"(d[5]), "=f"(d[6]), "=f"(d[7]), "=f"(d[8]), "=f"(d[9]), "=f"(d[10]), "=f"(d[11]), "=f"(d[12]), "=f"(d[13]), "=f"(d[14]), "=f"(d[15]), "=f"(d[16]), "=f"(d[17]), "=f"(d[18]), "=f"(d[19]), "=f"(d[20]), "=f"(d[21]), "=f"(d[22]), "=f"(d[23]), "=f"(d[24]), "=f"(d[25]), "=f"(d[26]), "=f"(d[27]), "=f"(d[28]), "=f"(d[29]), "=f"(d[30]), "=f"(d[31]), "=f"(d[32]), "=f"(d[33]), "=f"(d[34]), "=f"(d[35]), "=f"(d[36]), "=f"(d[37]), "=f"(d[38]), "=f"(d[39]), "=f"(d[40]), "=f"(d[41]), "=f"(d[42]), "=f"(d[43]), "=f"(d[44]), "=f"(d[45]), "=f"(d[46]), "=f"(d[47]), "=f"(d[48]), "=f"(d[49]), "=f"(d[50]), "=f"(d[51]), "=f"(d[52]), "=f"(d[53]), "=f"(d[54]), "=f"(d[55]), "=f"(d[56]), "=f"(d[57]), "=f"(d[58]), "=f"(d[59]), "=f"(d[60]), "=f"(d[61]), "=f"(d[62]), "=f"(d[63]), "=f"(d[64]), "=f"(d[65]), "=f"(d[66]), "=f"(d[67]), "=f"(d[68]), "=f"(d[69]), "=f"(d[70]), "=f"(d[71])
    : "r"(a), "r"(b), "n"(TA), "n"(OA / 16), "n"(OB / 16));
}

template<int OB>
__device__ __forceinline__ void mma_rs(float (&d)[72], uint32_t diag, uint32_t b) {
  asm volatile("{\n.reg .b64 db;\n.reg .b32 tb, th, z;\n"
    "add.u32 tb, %73, %74;\nmov.b32 th, 0x40000040;\nmov.b32 z, 0;\n"
    "mov.b64 db, {tb, th};\n"
    "wgmma.mma_async.sync.aligned.m64n144k16.f32.bf16.bf16 "
    "{%0, %1, %2, %3, %4, %5, %6, %7, %8, %9, %10, %11, %12, %13, %14, %15, %16, %17, %18, %19, %20, %21, %22, %23, %24, %25, %26, %27, %28, %29, %30, %31, %32, %33, %34, %35, %36, %37, %38, %39, %40, %41, %42, %43, %44, %45, %46, %47, %48, %49, %50, %51, %52, %53, %54, %55, %56, %57, %58, %59, %60, %61, %62, %63, %64, %65, %66, %67, %68, %69, %70, %71}, "
    "{%72, z, z, %72}, db, 1, 1, 1, 0;\n}\n"
    : "+f"(d[0]), "+f"(d[1]), "+f"(d[2]), "+f"(d[3]), "+f"(d[4]), "+f"(d[5]), "+f"(d[6]), "+f"(d[7]), "+f"(d[8]), "+f"(d[9]), "+f"(d[10]), "+f"(d[11]), "+f"(d[12]), "+f"(d[13]), "+f"(d[14]), "+f"(d[15]), "+f"(d[16]), "+f"(d[17]), "+f"(d[18]), "+f"(d[19]), "+f"(d[20]), "+f"(d[21]), "+f"(d[22]), "+f"(d[23]), "+f"(d[24]), "+f"(d[25]), "+f"(d[26]), "+f"(d[27]), "+f"(d[28]), "+f"(d[29]), "+f"(d[30]), "+f"(d[31]), "+f"(d[32]), "+f"(d[33]), "+f"(d[34]), "+f"(d[35]), "+f"(d[36]), "+f"(d[37]), "+f"(d[38]), "+f"(d[39]), "+f"(d[40]), "+f"(d[41]), "+f"(d[42]), "+f"(d[43]), "+f"(d[44]), "+f"(d[45]), "+f"(d[46]), "+f"(d[47]), "+f"(d[48]), "+f"(d[49]), "+f"(d[50]), "+f"(d[51]), "+f"(d[52]), "+f"(d[53]), "+f"(d[54]), "+f"(d[55]), "+f"(d[56]), "+f"(d[57]), "+f"(d[58]), "+f"(d[59]), "+f"(d[60]), "+f"(d[61]), "+f"(d[62]), "+f"(d[63]), "+f"(d[64]), "+f"(d[65]), "+f"(d[66]), "+f"(d[67]), "+f"(d[68]), "+f"(d[69]), "+f"(d[70]), "+f"(d[71])
    : "r"(diag), "r"(b), "n"(OB / 16));
}

#define PF_Q 2
#define PF_DT_END 200
#define SHIFT 1
#define N1 12
#define PF_W 1
#define PF_SLEEP 50
#define PF_DT 620
#define PF_T0 3000
#define PF_X 1
#define FAKE_KV 0
#define RED_STEP 1
#define EXP_START 3
#define EXP_END 16

__device__ __forceinline__ void store_acc_T(const float (&d)[72], uint32_t addr) {
  #pragma unroll
  for (int j = 0; j < 18; j += 2)
    stsm4t(addr + j * 1024, pack_bf16(d[4*j], d[4*j+1]), pack_bf16(d[4*j+2], d[4*j+3]),
           pack_bf16(d[4*j+4], d[4*j+5]), pack_bf16(d[4*j+6], d[4*j+7]));
}

template<bool IS_MAX>
__device__ __forceinline__ void warp_col_reduce(const uint32_t (&v)[18], uint32_t (&r3)[3], int lane) {
  #define OP(a, b) (IS_MAX ? max_bf16x2(a, b) : add_bf16x2(a, b))
  const bool b4 = lane & 16, b3 = lane & 8, b2 = lane & 4;
  uint32_t r1[9], r2[5];
  #pragma unroll
  for (int k = 0; k < 9; k++) {
    const uint32_t snd = b4 ? v[k] : v[k+9], kp = b4 ? v[k+9] : v[k];
    r1[k] = OP(kp, __shfl_xor_sync(0xffffffff, snd, 16));
  }
  #pragma unroll
  for (int k = 0; k < 4; k++) {
    const uint32_t snd = b3 ? r1[k] : r1[k+4], kp = b3 ? r1[k+4] : r1[k];
    r2[k] = OP(kp, __shfl_xor_sync(0xffffffff, snd, 8));
  }
  r2[4] = OP(r1[8], __shfl_xor_sync(0xffffffff, r1[8], 8));
  #pragma unroll
  for (int k = 0; k < 2; k++) {
    const uint32_t snd = b2 ? r2[k] : r2[k+2], kp = b2 ? r2[k+2] : r2[k];
    r3[k] = OP(kp, __shfl_xor_sync(0xffffffff, snd, 4));
  }
  r3[2] = OP(r2[4], __shfl_xor_sync(0xffffffff, r2[4], 4));
  #undef OP
}

struct Seg { int isq, head_or_k0, n; uint32_t lap; int laplen, lap0; };
__device__ __forceinline__ Seg seg_info(int n) {
  Seg s;
  s.isq = (n <= 3 || n == 6);
  s.head_or_k0 = n == 0 || n == 6 ? 3 : (n <= 3 ? n - 1 : (n == 4 ? 0 : (n == 5 ? N1 : (n == 7 ? N1 + 16 : N1 + 32))));
  s.n = n == 4 ? N1 : (n == 8 ? 35 - N1 : 16);
  const bool g = n == 2 || n == 3 || n == 5 || n == 7;
  s.lap = g ? 0x54321u : (n == 4 ? 0x1243u : 0x12435u);
  s.laplen = n == 4 ? 4 : 5;
  s.lap0 = n == 0 ? 4 : 0;
  return s;
}

__device__ __forceinline__ int part_stage(int n, int j) { return n == 8 && j < 3 ? j : -1; }
__device__ __forceinline__ int stage_k(int n, int j) { return n == 8 ? j - 3 : j; }

__global__ void __launch_bounds__(384, 1) fused_kernel(const __grid_constant__ Params P) {
  extern __shared__ __align__(1024) char smem_raw[];
  const uint32_t sb = (smem_u32(smem_raw) + 1023u) & ~1023u;
  const uint32_t full0 = sb + OFF_BAR, empty0 = full0 + 48, stg0 = full0 + 96, maxbar = full0 + 104, stgfree = full0 + 112;
  const uint32_t ordy = full0 + 144, pdone = full0 + 120;
  const uint32_t kvcnt = full0 + 128;
  const int tid = threadIdx.x;
  const int wg = __shfl_sync(0xffffffff, tid >> 7, 0);
  uint32_t rank; asm volatile("mov.u32 %0, %%cluster_ctarank;" : "=r"(rank));
  const int cl = blockIdx.x >> 1;
  const int blk = cl >> 5, b = ((cl >> 3) & 3) * 2 + rank, sub = cl & 7;
  const int sh = SHIFT ? blk : 0;
  uint4* const park = g_park + blockIdx.x * (4 * (PAIR / 16));

  if (tid == 0) {
    for (int i = 0; i < 6; i++) { mbar_init(full0 + 8*i, 1); mbar_init(empty0 + 8*i, 4); }
    mbar_init(stg0, 8); mbar_init(maxbar, 8); mbar_init(stgfree, 1); mbar_init(pdone, 1);
    for (int i = 0; i < 4; i++) mbar_init(ordy + 8*i, 1);
    asm volatile("fence.mbarrier_init.release.cluster;" ::: "memory");
  }
  if (tid < 288) asm volatile("st.shared.u32 [%0], %1;" :: "r"(sb + OFF_MAX + tid*4), "r"(0xff800000u) : "memory");
  if (tid == 300) asm volatile("st.shared.u32 [%0], %1;" :: "r"(kvcnt), "r"(0u) : "memory");
  TRINIT();
  __syncthreads();
  cluster_sync();

  if (wg == 2) {
    asm volatile("setmaxnreg.dec.sync.aligned.u32 40;");
    const int warp = __shfl_sync(0xffffffff, (tid >> 5) & 3, 0);
    const int lane = tid & 31;
    #define ACQ(s) do { mbar_wait(empty0 + 8*(s), (eph >> (s)) & 1); eph ^= 1u << (s); } while (0)
    #define VH(n) ((n) == 2 ? 0 : ((n) == 3 ? 1 : ((n) == 5 ? 2 : ((n) == 7 ? 3 : -1))))
    #define KH(n) ((n) == 1 ? 0 : ((n) == 2 ? 1 : ((n) == 4 ? 2 : ((n) == 6 || ((n) == 5 && sh) ? 3 : -1))))
    if (warp == 0) {
      uint32_t eph = 0x3Fu;
      uint64_t pol; asm volatile("createpolicy.fractional.L2::evict_first.b64 %0, 1.0;" : "=l"(pol));
      if (FAKE_KV) asm volatile("createpolicy.fractional.L2::evict_normal.b64 %0, 1.0;" : "=l"(pol));
      int nkv = 0;
      #define PARK_LOAD(slot, pair) asm volatile(ELECT_BEGIN "@p mbarrier.arrive.expect_tx.shared::cta.b64 _, [%2], %3;\n" \
          "@p cp.async.bulk.shared::cluster.global.mbarrier::complete_tx::bytes [%0], [%1], %3, [%2];\n}\n" \
          :: "r"(sb + (pair) * PAIR), "l"(park + (slot) * (PAIR / 16)), "r"(full0 + 8 * (pair)), "r"(PAIR) : "memory")
      #pragma unroll 1
      for (int n = 1 - sh; n < 9; n++) {
        if (n == 6 && sh) continue;
        const Seg sg = seg_info(n);
        const CUtensorMap* map = sg.isq ? &P.x[blk] : &P.os;
        const int row = (sg.isq ? 0 : blk * TOK) + b * SQ, k0 = sg.isq ? 0 : sg.head_or_k0;
        int lp = sg.lap0;
        #pragma unroll 1
        for (int j = 0; j < sg.n; j++) {
          const int s = (sg.lap >> (lp * 4)) & 15;
          const int ps = part_stage(n, j), kk = k0 + stage_k(n, j);
          if (ps >= 0) {
            if (ps == 2) mbar_wait(pdone, 0);
            ACQ(s);
            PARK_LOAD(ps, s);
          } else {
            if (!sg.isq && (kk & 15) == 0) mbar_wait(ordy + 8 * (kk >> 4), 0);
            ACQ(s);
            tma2d(sb + s * PAIR, map, kk * 64, row, full0 + 8*s, 18432 + 16384);
          }
          if (++lp == sg.laplen) lp = 0;
        }
        const int vh = VH(n), kh = KH(n);
        #pragma unroll 1
        for (int q = (vh < 0 ? 4 : 0); q < (kh < 0 ? 4 : 8); q++) {
          if (sh && n == 5 && q == 4) {
            ACQ(5);
            PARK_LOAD(3, 5);
          }
          const int s = (0x32432432u >> (q * 4)) & 15;
          const int head = (q < 4 ? vh : kh) * 8 + sub;
          ACQ(s);
          tma3d_hint(sb + s * PAIR, q < 4 ? &P.v[blk] : &P.k[blk], (FAKE_KV ? sub : b * 32 + head) * 512 + ((q < 4 ? q : q + 1) & 3) * 128, full0 + 8*s, pol, 32768);
          nkv++;
          asm volatile("st.volatile.shared.u32 [%0], %1;" :: "r"(kvcnt), "r"(nkv) : "memory");
        }
      }
    } else if (warp == 1) {
      uint32_t eph = 0x3Fu;
      int need = 0;
      #pragma unroll 1
      for (int n = 1 - sh; n < 9; n++) {
        if (n == 6 && sh) continue;
        const Seg sg = seg_info(n);
        const CUtensorMap* map = sg.isq ? &P.wq[blk] : &P.wo[blk];
        const int col = (sg.isq ? sg.head_or_k0 * 8 + sub : sub) * 128 + rank * 64, k0 = sg.isq ? 0 : sg.head_or_k0;
        int lp = sg.lap0;
        #pragma unroll 1
        for (int j = 0; j < sg.n; j++) {
          const int s = (sg.lap >> (lp * 4)) & 15;
          if (j == (n == 4 ? 0 : 1)) {
            #pragma unroll 1
            for (int spin = 0; spin < 1000000; spin++) {
              int cnt; asm volatile("ld.volatile.shared.u32 %0, [%1];" : "=r"(cnt) : "r"(kvcnt) : "memory");
              if (cnt >= need) break;
              __nanosleep(100);
            }
          }
          ACQ(s);
          if (part_stage(n, j) < 0) tma2d_mc(sb + s * PAIR + SLOT + rank * 8192, map, col, (k0 + stage_k(n, j)) * 64, full0 + 8*s);
          if (++lp == sg.laplen) lp = 0;
        }
        if (VH(n) >= 0) { eph ^= 0x18u; need += 4; }
        if (KH(n) >= 0) { eph ^= 0x14u; need += 4; }
        if (sh && n == 5) eph ^= 0x20u;
      }
    } else if (warp == 2) {
      uint32_t ph = 0;
      #define PARK_STORE(slot, pair) do { if (lane == 0) { mbar_wait(stg0, ph); \
          asm volatile("cp.async.bulk.global.shared::cta.bulk_group [%0], [%1], %2;" :: "l"(park + (slot) * (PAIR / 16)), "r"(sb + (pair) * PAIR), "r"(PAIR) : "memory"); \
          asm volatile("cp.async.bulk.commit_group;" ::: "memory"); \
          asm volatile("cp.async.bulk.wait_group.read 0;" ::: "memory"); \
          if (pair) { mbar_arrive_cta(empty0 + 40, 0, 2); mbar_arrive_cta(empty0 + 40, 1, 2); } else mbar_arrive(stgfree); } \
          ph ^= 1; __syncwarp(); } while (0)
      if (sh) PARK_STORE(3, 0);
      #pragma unroll 1
      for (int n = 0; n < 4; n++) {
        if (n == 2) PARK_STORE(0, 0);
        if (n >= 2) PARK_STORE(n - 1, 5);
        bar_sync<4, 288>();
        #pragma unroll
        for (int r = 0; r < 3; r++) {
          const int idx = r * 32 + lane;
          if (idx < 72) {
            float s0 = 0.f, s1 = 0.f;
            #pragma unroll
            for (int ww = 0; ww < 8; ww++) {
              uint32_t v; asm volatile("ld.shared.u32 %0, [%1];" : "=r"(v) : "r"(sb + OFF_SUM + ww * 288 + idx * 4));
              s0 += bf_lo(v); s1 += bf_hi(v);
            }
            asm volatile("st.shared.v2.f32 [%0], {%1, %2};" :: "r"(sb + OFF_INV + idx * 8), "f"(__fdividef(1.f, s0)), "f"(__fdividef(1.f, s1)) : "memory");
          }
        }
        bar_arrive<7, 160>();
        bar_arrive<8, 160>();
        if (lane == 0) {
          if (n == 3) { asm volatile("cp.async.bulk.wait_group 0;" ::: "memory"); asm volatile("fence.proxy.async.global;" ::: "memory"); mbar_arrive(pdone); }
          mbar_wait(stg0, ph);
          tma2d_store(&P.os, (n * 8 + sub) * 128, blk * TOK + b * SQ, sb);
          tma2d_store(&P.os, (n * 8 + sub) * 128 + 64, blk * TOK + b * SQ, sb + SLOT);
          asm volatile("cp.async.bulk.commit_group;" ::: "memory");
          asm volatile("cp.async.bulk.wait_group.read 0;" ::: "memory");
          mbar_arrive(stgfree);
          asm volatile("cp.async.bulk.wait_group 0;" ::: "memory");
          asm volatile("fence.proxy.async.global;" ::: "memory");
          asm volatile("red.release.gpu.global.add.u32 [%0], %1;" :: "l"(&g_cnt[(blk * 8 + b) * 4 + n]), "r"(1u) : "memory");
        }
        ph ^= 1;
        __syncwarp();
      }
      if (lane == 0) {
        mbar_wait(stg0, ph);
        tma2d_store(&P.out, blk * 1024 + sub * 128, b * SQ, sb);
        tma2d_store(&P.out, blk * 1024 + sub * 128 + 64, b * SQ, sb + SLOT);
        asm volatile("cp.async.bulk.commit_group;" ::: "memory");
        asm volatile("cp.async.bulk.wait_group.read 0;" ::: "memory");
      }
    } else {
      unsigned int epoch;
      asm volatile("ld.relaxed.gpu.global.u32 %0, [%1];" : "=r"(epoch) : "l"(&g_done) : "memory");
      const unsigned int target = 8u * ((epoch >> 7) + 1);
      const uint32_t ids = sh ? 0x7654210u : 0x7635421u, trig = sh ? 0xEC97510u : 0xECB9751u;
      const size_t bh0 = (size_t)(b * 32 + sub) * (512 * 256) + lane * 256;
      uint32_t v[PF_Q], c[PF_Q];
      #pragma unroll
      for (int i = 0; i < PF_Q; i++) { v[i] = 0; c[i] = target - 1; }
      int nrdy = 0, g = PF_W ? 0 : 7, part = 0, q = PF_LEAD ? 0 : 128;
      uint32_t tnext = (uint32_t)clock64() + PF_T0;
      #pragma unroll 1
      for (int spin = 0; spin < 100000 && (nrdy < 4 || g < 7); spin++) {
        #pragma unroll
        for (int i = 0; i < PF_Q; i++) {
          while ((int)((uint32_t)clock64() - tnext) < 0) __nanosleep(PF_SLEEP);
          tnext += PF_DT;
          { const uint32_t now = (uint32_t)clock64(); if ((int)(now - tnext) > 0) tnext = now; }
          int cnt; asm volatile("ld.volatile.shared.u32 %0, [%1];" : "=r"(cnt) : "r"(kvcnt) : "memory");
          const uint32_t done = __ballot_sync(0xffffffff, (int)(c[i] - target) >= 0) & 15u;
          while (nrdy < 4 && ((done >> nrdy) & 1)) {
            asm volatile("fence.acq_rel.gpu;" ::: "memory");
            asm volatile("fence.proxy.async.global;" ::: "memory");
            __syncwarp();
            if (lane == 0) mbar_arrive(ordy + 8 * nrdy);
            nrdy++;
          }
          if (cnt >= nrdy * 8 + 8) asm volatile("ld.relaxed.gpu.global.u32 %0, [%1];" : "=r"(c[i]) : "l"(&g_cnt[(blk * 8 + b) * 4 + (lane & 3)]) : "memory");
          const char* a = nullptr;
          if (q < cnt * 4) q = cnt * 4;
          if (g < 7 && cnt >= (int)((trig >> (g * 4)) & 15) * 2) {
            const int id = (ids >> (g * 4)) & 15;
            if (part < 4) {
              const int r = b * 128 + part * 32 + lane;
              a = id < 4 ? P.wqptr[blk] + (size_t)r * 8192 + (id * 8 + sub) * 256
                         : P.woptr[blk] + (size_t)((id - 4) * 1024 + r) * 2048 + sub * 256;
            } else {
              a = P.xptr[blk] + (size_t)(b * SQ + min((part - 4) * 32 + lane, SQ - 1)) * 2048 + sub * 256;
            }
            if (++part == (id < 4 && PF_X ? 9 : 4)) { part = 0; g++; }
          } else if (q < 128 && q < (cnt + PF_LEAD) * 4) {
            const int pr = q >> 2;
            a = ((pr & 4) ? P.vptr[blk] : P.kptr[blk]) + bh0 + (size_t)(pr >> 3) * (8 * 512 * 256) + (((pr & 4) ? pr : pr + 1) & 3) * 32768 + (q & 3) * 8192;
            q++;
          }
          if (a) {
            asm volatile("st.volatile.shared.u32 [%0], %1;" :: "r"(kvcnt + 8), "r"(v[i]) : "memory");
            asm volatile("ld.global.L2::256B.u32 %0, [%1];" : "=r"(v[i]) : "l"(a) : "memory");
          }
          if (q >= 128 && g >= 7) tnext -= PF_DT - PF_DT_END;
        }
      }
      #pragma unroll
      for (int i = 0; i < PF_Q; i++) asm volatile("st.volatile.shared.u32 [%0], %1;" :: "r"(kvcnt + 8), "r"(v[i]) : "memory");
      if (lane == 0) atomicAdd(&g_done, 1u);
    }
    __syncwarp();
    cluster_sync();
  } else {
    asm volatile("setmaxnreg.inc.sync.aligned.u32 232;");
    const int w = wg;
    int t128 = tid & 127;
    asm volatile("" : "+r"(t128));
    #define lane (t128 & 31)
    #define warp (t128 >> 5)
    const uint32_t st_base = sb + w * SLOT + (uint32_t)(((lane >> 4) * 8 + (lane & 7)) * 128 + (((2 * warp + ((lane >> 3) & 1)) ^ (lane & 7)) << 4));
    const uint32_t d0 = ((sb & 0x3FFFF) >> 4) | (64u << 16);
    const uint32_t d0w = d0 + w * 512, d0v = d0 + w * 1024;
    uint32_t rel_addr; asm("mapa.shared::cluster.u32 %0, %1, %2;" : "=r"(rel_addr) : "r"(empty0), "r"(t128 & 1));
    #define WAITF(s, flip) mbar_wait(full0 + 8*(s), ((fph >> (s)) & 1) ^ (flip))
    #define REL(s) asm volatile("{\n.reg .pred p;\nsetp.lt.u32 p, %1, 2;\n@p mbarrier.arrive.relaxed.cluster.shared::cluster.b64 _, [%0];\n}\n" :: "r"(rel_addr + 8*(s)), "r"(t128) : "memory")
    #define STG_ARRIVE() do { fence_async_smem(); __syncwarp(); if (lane == 0) mbar_arrive(stg0); } while (0)
    #define STG_FREE() do { mbar_wait(stgfree, sfp); sfp ^= 1; } while (0)
    #define TURN_WAIT() do { if (w) bar_sync<6, 256>(); else bar_sync<5, 256>(); } while (0)
    #define TURN_PASS() do { if (w) bar_arrive<5, 256>(); else bar_arrive<6, 256>(); } while (0)
    #define GMMA(acc, da, db, O, first) do { if (!(first)) fence_regs(acc); wg_fence(); \
        if (first) mma_init<1, (O) + SLOT, (O)>(acc, da, db); else mma<1, (O) + SLOT, (O)>(acc, da, db); \
        mma<1, (O) + SLOT + 2048, (O) + 32>(acc, da, db); mma<1, (O) + SLOT + 4096, (O) + 64>(acc, da, db); \
        mma<1, (O) + SLOT + 6144, (O) + 96>(acc, da, db); wg_commit(); } while (0)
    #define O_STSM() do { _Pragma("unroll") for (int c_ = 0; c_ < 9; c_++) \
        stsm4t(st_base + c_ * 2048, ok[4*c_], ok[4*c_+1], ok[4*c_+2], ok[4*c_+3]); } while (0)
    #define O_STORE() do { O_STSM(); STG_ARRIVE(); } while (0)
    #define SMMA(p) do { \
        mma_init<0, (p) * PAIR, 5 * PAIR>(s, d0w, d0);     mma<0, (p) * PAIR + 32, 5 * PAIR + 32>(s, d0w, d0); \
        mma<0, (p) * PAIR + 64, 5 * PAIR + 64>(s, d0w, d0); mma<0, (p) * PAIR + 96, 5 * PAIR + 96>(s, d0w, d0); \
        mma<0, (p) * PAIR + 16384, 5 * PAIR + SLOT>(s, d0w, d0);           mma<0, (p) * PAIR + 16384 + 32, 5 * PAIR + SLOT + 32>(s, d0w, d0); \
        mma<0, (p) * PAIR + 16384 + 64, 5 * PAIR + SLOT + 64>(s, d0w, d0); mma<0, (p) * PAIR + 16384 + 96, 5 * PAIR + SLOT + 96>(s, d0w, d0); } while (0)
    const float cs = 0.08838834764831845f * 1.4426950408889634f;
    uint32_t fph = 0, sfp = 0;
    uint32_t ok[36];
    #pragma unroll
    for (int i = 0; i < 36; i++) ok[i] = 0;
    TR(0); TRG(0);
    #pragma unroll 1
    for (int h = -sh; h < 5; h++) {
      const bool hasx = !(h == 1 || (h == 3 && sh));
      const int tb = 2 + (h < 0 ? 0 : h) * 11; (void)tb;
      if (hasx) {
        const Seg sg = seg_info(h <= 0 ? h + 1 : 2 * h);
        float a0[72];
        #pragma unroll
        for (int i = 0; i < 72; i++) a0[i] = 0.f;
        if (h > 0 && !w) bar_sync<5, 256>();
        int lp = sg.lap0, sprev = 0, j0 = 0;
        if (h == 4) {
          const uint32_t dg = (lane >> 3) == (lane & 3) ? ((lane & 4) ? 0x3f800000u : 0x00003f80u) : 0u;
          const uint32_t db = d0 + w * (SLOT / 16);
          const uint32_t g0 = warp == 0 ? dg : 0u, g1 = warp == 1 ? dg : 0u, g2 = warp == 2 ? dg : 0u, g3 = warp == 3 ? dg : 0u;
          #define FOLD(p) do { WAITF(p, 0); fence_regs(a0); wg_fence(); \
              mma_rs<(p) * PAIR>(a0, g0, db); mma_rs<(p) * PAIR + 32>(a0, g1, db); mma_rs<(p) * PAIR + 64>(a0, g2, db); mma_rs<(p) * PAIR + 96>(a0, g3, db); \
              wg_commit(); } while (0)
          FOLD(5); O_STSM(); FOLD(3); STG_ARRIVE(); wg_wait<1>(); REL(5); FOLD(4); wg_wait<1>(); REL(3); wg_wait<0>(); fence_regs(a0); REL(4);
          fph ^= 0x38u; lp = 3; j0 = 3;
        }
        #pragma unroll 1
        for (int j = j0; j < sg.n; j++) {
          const int s = (sg.lap >> (lp * 4)) & 15;
          WAITF(s, 0); fph ^= 1u << s;
          TRS((h < 0 ? 0 : h + 1) * 24 + j);
          const uint32_t off = s * (PAIR / 16);
          GMMA(a0, d0w + off, d0 + off, 0, false);
          if (h > 0 && j == 0) O_STSM();
          if (h > 0 && j == 1) STG_ARRIVE();
          wg_wait<1>();
          if (j > j0) REL(sprev);
          sprev = s;
          if (++lp == sg.laplen) lp = 0;
        }
        const bool toq = h == 0 || h == 3;
        if (h > 0 && !toq) STG_FREE();
        wg_wait<0>();
        fence_regs(a0);
        TR(tb);
        if (toq) bar_sync<3, 256>(); else REL(sprev);
        const float f = sg.isq ? cs : 1.f;
        #pragma unroll
        for (int i = 0; i < 72; i++) a0[i] *= f;
        store_acc_T(a0, st_base + (toq ? 5 * PAIR : 0));
        fence_async_smem();
        if (!toq) { __syncwarp(); if (lane == 0) mbar_arrive(stg0); }
        if (h >= 0 && h < 4 && w) bar_arrive<5, 256>();
      }
      if (h < 0 || h == 4) continue;
      const uint32_t hodd = h & 1;
      const uint32_t ma = sb + OFF_MAX + hodd * 576 + (lane & 3) * 144;
      uint32_t sp[3][36];
      uint32_t l2[18];
      uint32_t mx[18];
      TR(tb + 1);
      #pragma unroll
      for (int i = 0; i < 4; i++) {
        constexpr int KSL[4] = {3, 4, 2, 3};
        WAITF(KSL[i], i == 3);
        float s[72];
        TURN_WAIT();
        wg_fence();
        if (i == 0 || i == 3) { SMMA(3); } else if (i == 1) { SMMA(4); } else { SMMA(2); }
        wg_commit();
        if (i < 3 || !w) TURN_PASS();
        if (i == 0 && !hasx) O_STORE();
        if (i == 3 && h + sh > 0) STG_FREE();
        wg_wait<0>();
        fence_regs(s);
        REL(KSL[i]);
        if (i < 3) {
          #pragma unroll
          for (int j = 0; j < 18; j++) {
            sp[i][2*j] = pack_bf16(s[4*j], s[4*j+1]);
            sp[i][2*j+1] = pack_bf16(s[4*j+2], s[4*j+3]);
            const uint32_t m2 = max_bf16x2(sp[i][2*j], sp[i][2*j+1]);
            mx[j] = i ? max_bf16x2(mx[j], m2) : m2;
            asm volatile("" : "+r"(sp[i][2*j]), "+r"(sp[i][2*j+1]), "+r"(mx[j]) :: "memory");
          }
        } else {
          REL(5);
          #pragma unroll
          for (int c = 0; c < 9; c++) {
            const uint32_t k0 = pack_bf16(s[8*c], s[8*c+1]), k1 = pack_bf16(s[8*c+2], s[8*c+3]);
            const uint32_t k2 = pack_bf16(s[8*c+4], s[8*c+5]), k3 = pack_bf16(s[8*c+6], s[8*c+7]);
            stsm4t(st_base + c * 2048, k0, k1, k2, k3);
            mx[2*c] = max_bf16x2(mx[2*c], max_bf16x2(k0, k1));
            mx[2*c+1] = max_bf16x2(mx[2*c+1], max_bf16x2(k2, k3));
            asm volatile("" : "+r"(mx[2*c]), "+r"(mx[2*c+1]) :: "memory");
          }
        }
      }
      fph ^= 0x14u;
      TR(tb + 2);
      #define STORE_P(i) do { _Pragma("unroll") for (int c_ = 0; c_ < 9; c_++) \
          stsm4t(st_base + ((i) & 1) * PAIR + c_ * 2048, sp[(i)-1][4*c_], sp[(i)-1][4*c_+1], sp[(i)-1][4*c_+2], sp[(i)-1][4*c_+3]); } while (0)
      {
        float a0[72];
        uint32_t m0 = 0, m1 = 0;
        #define GSTEP(j) do { \
          constexpr int p_ = (j) % 5; \
          WAITF(1 + p_, ((j) / 5) & 1); \
          GMMA(a0, d0w, d0, (1 + p_) * PAIR, (j) == 0); \
          if ((j) == RED_STEP) { \
            uint32_t r3[3]; warp_col_reduce<true>(mx, r3, lane); \
            const int jb = (lane & 16) ? 9 : 0, j0 = jb + ((lane & 8) ? 4 : 0) + ((lane & 4) ? 2 : 0); \
            red_max_f32(ma + j0 * 8, bf_lo(r3[0]), true);      red_max_f32(ma + j0 * 8 + 4, bf_hi(r3[0]), true); \
            red_max_f32(ma + j0 * 8 + 8, bf_lo(r3[1]), true);  red_max_f32(ma + j0 * 8 + 12, bf_hi(r3[1]), true); \
            red_max_f32(ma + (jb + 8) * 8, bf_lo(r3[2]), !(lane & 12)); red_max_f32(ma + (jb + 8) * 8 + 4, bf_hi(r3[2]), !(lane & 12)); \
            __syncwarp(); if (lane == 0) mbar_arrive(maxbar); TR(tb + 3); } \
          if ((j) == EXP_START) mbar_wait(maxbar, hodd); \
          if ((j) >= EXP_START && (j) < EXP_END) { \
            _Pragma("unroll") for (int u = (((j) - EXP_START) * 36) / (EXP_END - EXP_START); u < (((j) - EXP_START + 1) * 36) / (EXP_END - EXP_START); u++) { \
              const int c = u >> 2, t = u & 3; \
              if (t == 0) { \
                const float4 m_ = lds128(ma + c * 16); \
                m0 = __byte_perm(__float_as_uint(m_.x), __float_as_uint(m_.y), 0x7632); \
                m1 = __byte_perm(__float_as_uint(m_.z), __float_as_uint(m_.w), 0x7632); \
                uint32_t k0, k1, k2, k3; \
                ldsm4t(st_base + c * 2048, k0, k1, k2, k3); \
                k0 = ex2_bf16x2_raw(sub_bf16x2(k0, m0)); k1 = ex2_bf16x2_raw(sub_bf16x2(k1, m0)); \
                k2 = ex2_bf16x2_raw(sub_bf16x2(k2, m1)); k3 = ex2_bf16x2_raw(sub_bf16x2(k3, m1)); \
                stsm4t(st_base + c * 2048, k0, k1, k2, k3); \
                l2[2*c] = add_bf16x2(k0, k1); l2[2*c+1] = add_bf16x2(k2, k3); \
                asm volatile("" : "+r"(l2[2*c]), "+r"(l2[2*c+1]) :: "memory"); \
              } else { \
                uint32_t (&q)[36] = sp[t ? t - 1 : 0]; \
                q[4*c]   = ex2_bf16x2(sub_bf16x2(q[4*c],   m0)); q[4*c+1] = ex2_bf16x2(sub_bf16x2(q[4*c+1], m0)); \
                q[4*c+2] = ex2_bf16x2(sub_bf16x2(q[4*c+2], m1)); q[4*c+3] = ex2_bf16x2(sub_bf16x2(q[4*c+3], m1)); \
                l2[2*c] = add_bf16x2(l2[2*c], add_bf16x2(q[4*c], q[4*c+1])); \
                l2[2*c+1] = add_bf16x2(l2[2*c+1], add_bf16x2(q[4*c+2], q[4*c+3])); \
                asm volatile("" : "+r"(q[4*c]), "+r"(q[4*c+1]), "+r"(q[4*c+2]), "+r"(q[4*c+3]), "+r"(l2[2*c]), "+r"(l2[2*c+1]) :: "memory"); \
              } \
            } } \
          if ((j) > 0) { wg_wait<1>(); if ((j) < 15) REL(1 + ((j) + 4) % 5); } } while (0)
        GSTEP(0); GSTEP(1); GSTEP(2); GSTEP(3); GSTEP(4); GSTEP(5); GSTEP(6); GSTEP(7);
        GSTEP(8); GSTEP(9); GSTEP(10); GSTEP(11); GSTEP(12); GSTEP(13); GSTEP(14); GSTEP(15);
        fph ^= 0x3Cu;
        WAITF(2, 0);
        fence_async_smem();
        bar_sync<3, 256>();
        wg_wait<0>();
        fence_regs(a0);
        if (w) bar_arrive<10, 256>();
        TR(tb + 4);
        if (h < 2) {
          #pragma unroll
          for (int i = 0; i < 72; i++) a0[i] *= cs;
        }
        store_acc_T(a0, st_base + 5 * PAIR);
        TR(tb + 5);
      }
      float o[72];
      #define PVSTEP(i) do { \
        constexpr int v_ = (i) == 3 ? 2 : 2 + (i), pb_ = ((i) & 1) * PAIR; \
        if ((i) > 0) { \
          if (!w) { bar_sync<9 + ((i) & 1), 256>(); STORE_P((i) ? (i) : 1); } \
          if ((i) == 2) { \
            uint32_t r3[3]; \
            warp_col_reduce<false>(l2, r3, lane); \
            const int jb = (lane & 16) ? 9 : 0, j0 = jb + ((lane & 8) ? 4 : 0) + ((lane & 4) ? 2 : 0); \
            const uint32_t sa = sb + OFF_SUM + (w * 4 + warp) * 288 + (lane & 3) * 72; \
            asm volatile("st.shared.u32 [%0], %1;" :: "r"(sa + j0 * 4), "r"(r3[0]) : "memory"); \
            asm volatile("st.shared.u32 [%0], %1;" :: "r"(sa + j0 * 4 + 4), "r"(r3[1]) : "memory"); \
            asm volatile("st.shared.u32 [%0], %1;" :: "r"(sa + (jb + 8) * 4), "r"(r3[2]) : "memory"); \
            if (t128 < 72) asm volatile("st.shared.u32 [%0], %1;" :: "r"(sb + OFF_MAX + (hodd ^ 1) * 576 + w * 288 + t128 * 4), "r"(0xff800000u) : "memory"); \
            bar_arrive<4, 288>(); } \
          WAITF(v_, (i) == 3); \
          if (!w) fence_async_smem(); \
          if ((i) == 1 && h >= 2) { __syncwarp(); if (lane == 0) mbar_arrive(stg0); }     \
          wg_wait<0>(); \
          REL(1 + (i)); \
        } \
        if (!w) { if ((i) > 0) bar_sync<5, 256>(); } else { \
          if ((i) > 0 && (i) < 3) bar_arrive<10 - ((i) & 1), 256>(); \
          bar_sync<6, 256>(); \
          if ((i) < 3) STORE_P((i) < 3 ? (i) + 1 : 1); \
        } \
        if ((i) > 0) fence_regs(o); \
        wg_fence(); \
        if ((i) == 0) mma_init<1, v_ * PAIR, pb_>(o, d0v, d0); else mma<1, v_ * PAIR, pb_>(o, d0v, d0); \
        mma<1, v_ * PAIR + 2048, pb_ + 32>(o, d0v, d0); mma<1, v_ * PAIR + 4096, pb_ + 64>(o, d0v, d0); mma<1, v_ * PAIR + 6144, pb_ + 96>(o, d0v, d0); \
        mma<1, v_ * PAIR + 8192, pb_ + SLOT>(o, d0v, d0);       mma<1, v_ * PAIR + 10240, pb_ + SLOT + 32>(o, d0v, d0); \
        mma<1, v_ * PAIR + 12288, pb_ + SLOT + 64>(o, d0v, d0); mma<1, v_ * PAIR + 14336, pb_ + SLOT + 96>(o, d0v, d0); \
        wg_commit(); \
        if (w && (i) < 3) fence_async_smem(); \
        TURN_PASS(); \
        TR(tb + 6 + (i)); } while (0)
      PVSTEP(0);
      PVSTEP(1);
      PVSTEP(2);
      PVSTEP(3);
      fph ^= 0x18u;
      {
        if (sh && h == 2) { WAITF(5, 0); fph ^= 0x20u; }
        if (w) bar_sync<8, 160>(); else bar_sync<7, 160>();
        float4 iv[9];
        #pragma unroll
        for (int j = 0; j < 9; j++) iv[j] = lds128(sb + OFF_INV + (lane & 3) * 144 + j * 16);
        wg_wait<0>();
        fence_regs(o);
        REL(2); REL(1);
        #pragma unroll
        for (int j = 0; j < 9; j++) {
          ok[4*j]   = pack_bf16(o[8*j] * iv[j].x, o[8*j+1] * iv[j].y);   ok[4*j+1] = pack_bf16(o[8*j+2] * iv[j].x, o[8*j+3] * iv[j].y);
          ok[4*j+2] = pack_bf16(o[8*j+4] * iv[j].z, o[8*j+5] * iv[j].w); ok[4*j+3] = pack_bf16(o[8*j+6] * iv[j].z, o[8*j+7] * iv[j].w);
        }
      }
      TR(tb + 10);
    }
    TR(56);
    cluster_sync();
    TR(57); TRG(1); TRDUMP(); TRSDUMP();
    #undef lane
    #undef warp
  }
}

typedef CUresult (*PFN_enc)(CUtensorMap*, CUtensorMapDataType, cuuint32_t, void*, const cuuint64_t*, const cuuint64_t*,
                            const cuuint32_t*, const cuuint32_t*, CUtensorMapInterleave, CUtensorMapSwizzle,
                            CUtensorMapL2promotion, CUtensorMapFloatOOBfill);

void enc2d(PFN_enc enc, CUtensorMap* m, const void* p, uint64_t cols, uint64_t rows, uint32_t box_rows) {
  cuuint64_t dims[2] = {cols, rows}; cuuint64_t st[1] = {cols * 2};
  cuuint32_t box[2] = {64, box_rows}; cuuint32_t es[2] = {1, 1};
  enc(m, CU_TENSOR_MAP_DATA_TYPE_BFLOAT16, 2, (void*)p, dims, st, box, es, CU_TENSOR_MAP_INTERLEAVE_NONE,
      CU_TENSOR_MAP_SWIZZLE_128B, CU_TENSOR_MAP_L2_PROMOTION_L2_128B, CU_TENSOR_MAP_FLOAT_OOB_FILL_NONE);
}
void enc3d(PFN_enc enc, CUtensorMap* m, const void* p, uint64_t cols, uint64_t rows) {
  cuuint64_t dims[3] = {64, rows, cols / 64}; cuuint64_t st[2] = {cols * 2, 128};
  cuuint32_t box[3] = {64, 128, 2}; cuuint32_t es[3] = {1, 1, 1};
  enc(m, CU_TENSOR_MAP_DATA_TYPE_BFLOAT16, 3, (void*)p, dims, st, box, es, CU_TENSOR_MAP_INTERLEAVE_NONE,
      CU_TENSOR_MAP_SWIZZLE_128B, CU_TENSOR_MAP_L2_PROMOTION_L2_256B, CU_TENSOR_MAP_FLOAT_OOB_FILL_NONE);
}

}

extern "C" void kernel_launch(void* const* d_in, const int* in_sizes, int n_in, void* d_out, int out_size) {
  (void)in_sizes; (void)n_in; (void)out_size;
  void* fn = nullptr; cudaDriverEntryPointQueryResult q;
  cudaGetDriverEntryPoint("cuTensorMapEncodeTiled", &fn, cudaEnableDefault, &q);
  PFN_enc enc = (PFN_enc)fn;
  void* oscr = nullptr; cudaGetSymbolAddress(&oscr, g_oscr);
  Params P;
  for (int i = 0; i < 2; i++) {
    enc2d(enc, &P.x[i], d_in[5*i + 0], 1024, TOK, SQ);
    enc3d(enc, &P.k[i], d_in[5*i + 1], 128, 8 * 32 * 512);
    enc3d(enc, &P.v[i], d_in[5*i + 2], 128, 8 * 32 * 512);
    enc2d(enc, &P.wq[i], d_in[5*i + 3], 4096, 1024, 64);
    enc2d(enc, &P.wo[i], d_in[5*i + 4], 1024, 4096, 64);
    P.kptr[i] = (const char*)d_in[5*i + 1]; P.vptr[i] = (const char*)d_in[5*i + 2];
    P.xptr[i] = (const char*)d_in[5*i + 0];
    P.wqptr[i] = (const char*)d_in[5*i + 3]; P.woptr[i] = (const char*)d_in[5*i + 4];
  }
  P.zero = 0;
  enc2d(enc, &P.os, oscr, 4096, 2 * TOK, SQ);
  enc2d(enc, &P.out, d_out, 2048, TOK, SQ);
  cudaFuncSetAttribute(fused_kernel, cudaFuncAttributeMaxDynamicSharedMemorySize, SMEM_BYTES);
  cudaLaunchConfig_t cfg = {};
  cfg.gridDim = dim3(NCTA); cfg.blockDim = dim3(384); cfg.dynamicSmemBytes = SMEM_BYTES; cfg.stream = cudaStreamPerThread;
  cudaLaunchAttribute at[1];
  at[0].id = cudaLaunchAttributeClusterDimension; at[0].val.clusterDim.x = 2; at[0].val.clusterDim.y = 1; at[0].val.clusterDim.z = 1;
  cfg.attrs = at; cfg.numAttrs = 1;
  cudaLaunchKernelEx(&cfg, fused_kernel, P);
}
```

```cpp
#include <cuda_runtime.h>
#include <cuda.h>
#include <cuda_bf16.h>
#include <stdint.h>

namespace {

constexpr int SQ = 144;
constexpr int TOK = 1152;
constexpr int SLOT = 18432;
constexpr int NSLOT = 12;
constexpr int PAIR = 2 * SLOT;
constexpr int OFF_BAR = NSLOT * SLOT;
constexpr int OFF_MAX = OFF_BAR + 256;
constexpr int OFF_SUM = OFF_MAX + 2 * 576;
constexpr int OFF_INV = OFF_SUM + 8 * 288;
constexpr int OFF_TR = OFF_INV + 576;
constexpr int SMEM_BYTES = OFF_TR + 1024 + 2560 + 1024;
constexpr int NCTA = 128;
#define PF_LEAD 0

struct alignas(64) Params {
  CUtensorMap x[2], wq[2], k[2], v[2], wo[2], os, out, oss;
  const char* kptr[2];
  const char* vptr[2];
  const char* xptr[2];
  const char* wqptr[2];
  const char* woptr[2];
  uint32_t zero;
};

__device__ __nv_bfloat16 g_oscr[2 * TOK * 4096];
__device__ uint4 g_park[NCTA * 4 * (PAIR / 16)];
__device__ unsigned int g_cnt[64];
__device__ unsigned int g_done;

#define WID (cl * 2 + rank)
#define TR(idx)
#define TRG(i)
#define TRDUMP()
#define TRS(i)
#define EV(i)
#define TRSDUMP()
#define TRINIT()
__device__ __forceinline__ uint32_t smem_u32(const void* p) { return (uint32_t)__cvta_generic_to_shared(p); }
__device__ __forceinline__ void mbar_init(uint32_t bar, int cnt) {
  asm volatile("mbarrier.init.shared::cta.b64 [%0], %1;" :: "r"(bar), "r"(cnt));
}
__device__ __forceinline__ void mbar_arrive(uint32_t bar) {
  asm volatile("mbarrier.arrive.shared::cta.b64 _, [%0];" :: "r"(bar) : "memory");
}
__device__ __forceinline__ void mbar_arrive_cta(uint32_t bar, uint32_t cta, uint32_t cnt) {
  asm volatile("{\n.reg .b32 ra;\nmapa.shared::cluster.u32 ra, %0, %1;\n"
               "mbarrier.arrive.shared::cluster.b64 _, [ra], %2;\n}\n" :: "r"(bar), "r"(cta), "r"(cnt) : "memory");
}
__device__ __forceinline__ void mbar_wait(uint32_t bar, uint32_t parity) {
  asm volatile("{\n.reg .pred p;\n.reg .u32 c;\nmov.u32 c, 0;\n"
    "LAB_WAIT:\n"
    "mbarrier.try_wait.parity.shared::cta.b64 p, [%0], %1;\n"
    "@p bra DONE;\n"
    "add.u32 c, c, 1;\n"
    "setp.lt.u32 p, c, 400000;\n"
    "@p bra LAB_WAIT;\n"
    "DONE:\n}\n" :: "r"(bar), "r"(parity) : "memory");
}
#define ELECT_BEGIN "{\n.reg .pred p;\nelect.sync _|p, 0xffffffff;\n"
__device__ __forceinline__ void tma2d(uint32_t dst, const CUtensorMap* map, int c0, int c1, uint32_t bar, uint32_t bytes) {
  asm volatile(ELECT_BEGIN "@p mbarrier.arrive.expect_tx.shared::cta.b64 _, [%2], %5;\n"
    "@p cp.async.bulk.tensor.2d.shared::cluster.global.mbarrier::complete_tx::bytes [%0], [%1, {%3, %4}], [%2];\n}\n"
    :: "r"(dst), "l"(map), "r"(bar), "r"(c0), "r"(c1), "r"(bytes) : "memory");
}
__device__ __forceinline__ void tma2d_mc(uint32_t dst, const CUtensorMap* map, int c0, int c1, uint32_t bar) {
  asm volatile(ELECT_BEGIN
    "@p cp.async.bulk.tensor.2d.shared::cluster.global.mbarrier::complete_tx::bytes.multicast::cluster [%0], [%1, {%3, %4}], [%2], %5;\n}\n"
    :: "r"(dst), "l"(map), "r"(bar), "r"(c0), "r"(c1), "h"((uint16_t)3) : "memory");
}
__device__ __forceinline__ void tma2d(uint32_t dst, const CUtensorMap* map, int c0, int c1, uint32_t bar, uint32_t bytes, uint64_t pol) {
  asm volatile(ELECT_BEGIN "@p mbarrier.arrive.expect_tx.shared::cta.b64 _, [%2], %5;\n"
    "@p cp.async.bulk.tensor.2d.shared::cluster.global.mbarrier::complete_tx::bytes.L2::cache_hint [%0], [%1, {%3, %4}], [%2], %6;\n}\n"
    :: "r"(dst), "l"(map), "r"(bar), "r"(c0), "r"(c1), "r"(bytes), "l"(pol) : "memory");
}
__device__ __forceinline__ void tma2d_mc(uint32_t dst, const CUtensorMap* map, int c0, int c1, uint32_t bar, uint64_t pol) {
  asm volatile(ELECT_BEGIN
    "@p cp.async.bulk.tensor.2d.shared::cluster.global.mbarrier::complete_tx::bytes.multicast::cluster.L2::cache_hint [%0], [%1, {%3, %4}], [%2], %5, %6;\n}\n"
    :: "r"(dst), "l"(map), "r"(bar), "r"(c0), "r"(c1), "h"((uint16_t)3), "l"(pol) : "memory");
}
__device__ __forceinline__ void tma3d_hint(uint32_t dst, const CUtensorMap* map, int c1, uint32_t bar, uint64_t pol, uint32_t bytes) {
  asm volatile(ELECT_BEGIN "@p mbarrier.arrive.expect_tx.shared::cta.b64 _, [%2], %6;\n"
    "@p cp.async.bulk.tensor.3d.shared::cluster.global.mbarrier::complete_tx::bytes.L2::cache_hint [%0], [%1, {%3, %4, %3}], [%2], %5;\n}\n"
    :: "r"(dst), "l"(map), "r"(bar), "r"(0), "r"(c1), "l"(pol), "r"(bytes) : "memory");
}
__device__ __forceinline__ void tma2d_store(const CUtensorMap* map, int c0, int c1, uint32_t src) {
  asm volatile("cp.async.bulk.tensor.2d.global.shared::cta.bulk_group [%0, {%1, %2}], [%3];"
    :: "l"(map), "r"(c0), "r"(c1), "r"(src) : "memory");
}
__device__ __forceinline__ void sched_sep(uint32_t zero) {
  asm volatile("{\n.reg .pred p;\n.reg .u32 c;\nSEP_L:\n.pragma \"nounroll\";\nmov.u32 c, %%clock;\nsetp.lt.u32 p, c, %0;\n@p bra SEP_L;\n}\n" :: "r"(zero) : "memory");
}
__device__ __forceinline__ void wg_fence() { asm volatile("wgmma.fence.sync.aligned;" ::: "memory"); }
__device__ __forceinline__ void wg_commit() { asm volatile("wgmma.commit_group.sync.aligned;" ::: "memory"); }
template<int N> __device__ __forceinline__ void wg_wait() { asm volatile("wgmma.wait_group.sync.aligned %0;" :: "n"(N) : "memory"); }
__device__ __forceinline__ void fence_regs(float (&d)[72]) {
  #pragma unroll
  for (int i = 0; i < 72; i++) asm volatile("" : "+f"(d[i]) :: "memory");
}
__device__ __forceinline__ void fence_async_smem() { asm volatile("fence.proxy.async.shared::cta;" ::: "memory"); }
template<int ID, int N> __device__ __forceinline__ void bar_sync() { asm volatile("bar.sync %0, %1;" :: "n"(ID), "n"(N) : "memory"); }
__device__ __forceinline__ void cluster_sync() {
  asm volatile("barrier.cluster.arrive.relaxed.aligned;\nbarrier.cluster.wait.aligned;" ::: "memory");
}
__device__ __forceinline__ uint32_t pack_bf16(float lo, float hi) {
  uint32_t r; asm("cvt.rn.bf16x2.f32 %0, %1, %2;" : "=r"(r) : "f"(hi), "f"(lo)); return r;
}
__device__ __forceinline__ uint32_t max_bf16x2(uint32_t a, uint32_t b) {
  uint32_t r; asm("max.bf16x2 %0, %1, %2;" : "=r"(r) : "r"(a), "r"(b)); return r;
}
__device__ __forceinline__ uint32_t add_bf16x2(uint32_t a, uint32_t b) {
  uint32_t r; asm("add.rn.bf16x2 %0, %1, %2;" : "=r"(r) : "r"(a), "r"(b)); return r;
}
__device__ __forceinline__ uint32_t sub_bf16x2(uint32_t a, uint32_t b) {
  uint32_t r; asm("sub.rn.bf16x2 %0, %1, %2;" : "=r"(r) : "r"(a), "r"(b)); return r;
}
__device__ __forceinline__ uint32_t ex2_bf16x2(uint32_t a) {
  uint32_t r;
  asm("{\n.reg .b32 t;\nex2.approx.ftz.bf16x2 t, %1;\nmax.NaN.bf16x2 %0, t, %2;\n}\n" : "=r"(r) : "r"(a), "r"(0u));
  return r;
}
__device__ __forceinline__ uint32_t ex2_bf16x2_raw(uint32_t a) {
  uint32_t r; asm("ex2.approx.ftz.bf16x2 %0, %1;" : "=r"(r) : "r"(a)); return r;
}
__device__ __forceinline__ void ex2_halves(uint32_t a, uint16_t& lo, uint16_t& hi) {
  asm volatile("{\n.reg .b16 l, h;\nmov.b32 {l, h}, %2;\nex2.approx.ftz.bf16 %0, l;\nex2.approx.ftz.bf16 %1, h;\n}\n" : "=h"(lo), "=h"(hi) : "r"(a));
}
__device__ __forceinline__ uint32_t pack_halves(uint16_t lo, uint16_t hi) {
  uint32_t r; asm volatile("mov.b32 %0, {%1, %2};" : "=r"(r) : "h"(lo), "h"(hi)); return r;
}
__device__ __forceinline__ uint32_t pack_halves_pin(uint16_t lo, uint16_t hi) {
  uint32_t r; asm volatile("{\n.reg .b32 t;\nmov.b32 t, {%1, %2};\nmax.NaN.bf16x2 %0, t, %3;\n}\n" : "=r"(r) : "h"(lo), "h"(hi), "r"(0u)); return r;
}
__device__ __forceinline__ void ldsm4t(uint32_t addr, uint32_t& a, uint32_t& b, uint32_t& c, uint32_t& d) {
  asm volatile("ldmatrix.sync.aligned.m8n8.x4.trans.shared.b16 {%0, %1, %2, %3}, [%4];"
    : "=r"(a), "=r"(b), "=r"(c), "=r"(d) : "r"(addr));
}
__device__ __forceinline__ float bf_lo(uint32_t v) { return __uint_as_float(v << 16); }
__device__ __forceinline__ float bf_hi(uint32_t v) { return __uint_as_float(v & 0xffff0000u); }
__device__ __forceinline__ void stsm4t(uint32_t addr, uint32_t a, uint32_t b, uint32_t c, uint32_t d) {
  asm volatile("stmatrix.sync.aligned.m8n8.x4.trans.shared.b16 [%0], {%1, %2, %3, %4};"
    :: "r"(addr), "r"(a), "r"(b), "r"(c), "r"(d));
}
__device__ __forceinline__ float4 lds128(uint32_t addr) {
  float4 v; asm volatile("ld.shared.v4.f32 {%0, %1, %2, %3}, [%4];" : "=f"(v.x), "=f"(v.y), "=f"(v.z), "=f"(v.w) : "r"(addr)); return v;
}
__device__ __forceinline__ void red_max_f32(uint32_t addr, float v, bool on) {
  asm volatile("{\n.reg .pred p, q, e;\nsetp.ne.b32 e, %2, 0;\nsetp.ge.and.s32 p|q, %1, 0, e;\n"
               "@p red.shared.max.s32 [%0], %1;\n@q red.shared.min.u32 [%0], %1;\n}\n"
               :: "r"(addr), "r"(__float_as_uint(v)), "r"((uint32_t)on) : "memory");
}
template<int ID, int N> __device__ __forceinline__ void bar_arrive() { asm volatile("bar.arrive %0, %1;" :: "n"(ID), "n"(N) : "memory"); }

template<int TA, int OA, int OB>
__device__ __forceinline__ void mma(float (&d)[72], uint32_t a, uint32_t b) {
  asm volatile("{\n.reg .b64 da, db;\n.reg .b32 ta, tb, th;\n"
    "add.u32 ta, %72, %75;\nadd.u32 tb, %73, %76;\nmov.b32 th, 0x40000040;\n"
    "mov.b64 da, {ta, th};\nmov.b64 db, {tb, th};\n"
    "wgmma.mma_async.sync.aligned.m64n144k16.f32.bf16.bf16 "
    "{%0, %1, %2, %3, %4, %5, %6, %7, %8, %9, %10, %11, %12, %13, %14, %15, %16, %17, %18, %19, %20, %21, %22, %23, %24, %25, %26, %27, %28, %29, %30, %31, %32, %33, %34, %35, %36, %37, %38, %39, %40, %41, %42, %43, %44, %45, %46, %47, %48, %49, %50, %51, %52, %53, %54, %55, %56, %57, %58, %59, %60, %61, %62, %63, %64, %65, %66, %67, %68, %69, %70, %71}, "
    "da, db, 1, 1, 1, %74, 0;\n}\n"
    : "+f"(d[0]), "+f"(d[1]), "+f"(d[2]), "+f"(d[3]), "+f"(d[4]), "+f"(d[5]), "+f"(d[6]), "+f"(d[7]), "+f"(d[8]), "+f"(d[9]), "+f"(d[10]), "+f"(d[11]), "+f"(d[12]), "+f"(d[13]), "+f"(d[14]), "+f"(d[15]), "+f"(d[16]), "+f"(d[17]), "+f"(d[18]), "+f"(d[19]), "+f"(d[20]), "+f"(d[21]), "+f"(d[22]), "+f"(d[23]), "+f"(d[24]), "+f"(d[25]), "+f"(d[26]), "+f"(d[27]), "+f"(d[28]), "+f"(d[29]), "+f"(d[30]), "+f"(d[31]), "+f"(d[32]), "+f"(d[33]), "+f"(d[34]), "+f"(d[35]), "+f"(d[36]), "+f"(d[37]), "+f"(d[38]), "+f"(d[39]), "+f"(d[40]), "+f"(d[41]), "+f"(d[42]), "+f"(d[43]), "+f"(d[44]), "+f"(d[45]), "+f"(d[46]), "+f"(d[47]), "+f"(d[48]), "+f"(d[49]), "+f"(d[50]), "+f"(d[51]), "+f"(d[52]), "+f"(d[53]), "+f"(d[54]), "+f"(d[55]), "+f"(d[56]), "+f"(d[57]), "+f"(d[58]), "+f"(d[59]), "+f"(d[60]), "+f"(d[61]), "+f"(d[62]), "+f"(d[63]), "+f"(d[64]), "+f"(d[65]), "+f"(d[66]), "+f"(d[67]), "+f"(d[68]), "+f"(d[69]), "+f"(d[70]), "+f"(d[71])
    : "r"(a), "r"(b), "n"(TA), "n"(OA / 16), "n"(OB / 16));
}

template<int TA, int OA, int OB>
__device__ __forceinline__ void mma_init(float (&d)[72], uint32_t a, uint32_t b) {
  asm volatile("{\n.reg .b64 da, db;\n.reg .b32 ta, tb, th;\n"
    "add.u32 ta, %72, %75;\nadd.u32 tb, %73, %76;\nmov.b32 th, 0x40000040;\n"
    "mov.b64 da, {ta, th};\nmov.b64 db, {tb, th};\n"
    "wgmma.mma_async.sync.aligned.m64n144k16.f32.bf16.bf16 "
    "{%0, %1, %2, %3, %4, %5, %6, %7, %8, %9, %10, %11, %12, %13, %14, %15, %16, %17, %18, %19, %20, %21, %22, %23, %24, %25, %26, %27, %28, %29, %30, %31, %32, %33, %34, %35, %36, %37, %38, %39, %40, %41, %42, %43, %44, %45, %46, %47, %48, %49, %50, %51, %52, %53, %54, %55, %56, %57, %58, %59, %60, %61, %62, %63, %64, %65, %66, %67, %68, %69, %70, %71}, "
    "da, db, 0, 1, 1, %74, 0;\n}\n"
    : "=f"(d[0]), "=f"(d[1]), "=f"(d[2]), "=f"(d[3]), "=f"(d[4]), "=f"(d[5]), "=f"(d[6]), "=f"(d[7]), "=f"(d[8]), "=f"(d[9]), "=f"(d[10]), "=f"(d[11]), "=f"(d[12]), "=f"(d[13]), "=f"(d[14]), "=f"(d[15]), "=f"(d[16]), "=f"(d[17]), "=f"(d[18]), "=f"(d[19]), "=f"(d[20]), "=f"(d[21]), "=f"(d[22]), "=f"(d[23]), "=f"(d[24]), "=f"(d[25]), "=f"(d[26]), "=f"(d[27]), "=f"(d[28]), "=f"(d[29]), "=f"(d[30]), "=f"(d[31]), "=f"(d[32]), "=f"(d[33]), "=f"(d[34]), "=f"(d[35]), "=f"(d[36]), "=f"(d[37]), "=f"(d[38]), "=f"(d[39]), "=f"(d[40]), "=f"(d[41]), "=f"(d[42]), "=f"(d[43]), "=f"(d[44]), "=f"(d[45]), "=f"(d[46]), "=f"(d[47]), "=f"(d[48]), "=f"(d[49]), "=f"(d[50]), "=f"(d[51]), "=f"(d[52]), "=f"(d[53]), "=f"(d[54]), "=f"(d[55]), "=f"(d[56]), "=f"(d[57]), "=f"(d[58]), "=f"(d[59]), "=f"(d[60]), "=f"(d[61]), "=f"(d[62]), "=f"(d[63]), "=f"(d[64]), "=f"(d[65]), "=f"(d[66]), "=f"(d[67]), "=f"(d[68]), "=f"(d[69]), "=f"(d[70]), "=f"(d[71])
    : "r"(a), "r"(b), "n"(TA), "n"(OA / 16), "n"(OB / 16));
}

template<int OB>
__device__ __forceinline__ void mma_rs(float (&d)[72], uint32_t diag, uint32_t b) {
  asm volatile("{\n.reg .b64 db;\n.reg .b32 tb, th, z;\n"
    "add.u32 tb, %73, %74;\nmov.b32 th, 0x40000040;\nmov.b32 z, 0;\n"
    "mov.b64 db, {tb, th};\n"
    "wgmma.mma_async.sync.aligned.m64n144k16.f32.bf16.bf16 "
    "{%0, %1, %2, %3, %4, %5, %6, %7, %8, %9, %10, %11, %12, %13, %14, %15, %16, %17, %18, %19, %20, %21, %22, %23, %24, %25, %26, %27, %28, %29, %30, %31, %32, %33, %34, %35, %36, %37, %38, %39, %40, %41, %42, %43, %44, %45, %46, %47, %48, %49, %50, %51, %52, %53, %54, %55, %56, %57, %58, %59, %60, %61, %62, %63, %64, %65, %66, %67, %68, %69, %70, %71}, "
    "{%72, z, z, %72}, db, 1, 1, 1, 0;\n}\n"
    : "+f"(d[0]), "+f"(d[1]), "+f"(d[2]), "+f"(d[3]), "+f"(d[4]), "+f"(d[5]), "+f"(d[6]), "+f"(d[7]), "+f"(d[8]), "+f"(d[9]), "+f"(d[10]), "+f"(d[11]), "+f"(d[12]), "+f"(d[13]), "+f"(d[14]), "+f"(d[15]), "+f"(d[16]), "+f"(d[17]), "+f"(d[18]), "+f"(d[19]), "+f"(d[20]), "+f"(d[21]), "+f"(d[22]), "+f"(d[23]), "+f"(d[24]), "+f"(d[25]), "+f"(d[26]), "+f"(d[27]), "+f"(d[28]), "+f"(d[29]), "+f"(d[30]), "+f"(d[31]), "+f"(d[32]), "+f"(d[33]), "+f"(d[34]), "+f"(d[35]), "+f"(d[36]), "+f"(d[37]), "+f"(d[38]), "+f"(d[39]), "+f"(d[40]), "+f"(d[41]), "+f"(d[42]), "+f"(d[43]), "+f"(d[44]), "+f"(d[45]), "+f"(d[46]), "+f"(d[47]), "+f"(d[48]), "+f"(d[49]), "+f"(d[50]), "+f"(d[51]), "+f"(d[52]), "+f"(d[53]), "+f"(d[54]), "+f"(d[55]), "+f"(d[56]), "+f"(d[57]), "+f"(d[58]), "+f"(d[59]), "+f"(d[60]), "+f"(d[61]), "+f"(d[62]), "+f"(d[63]), "+f"(d[64]), "+f"(d[65]), "+f"(d[66]), "+f"(d[67]), "+f"(d[68]), "+f"(d[69]), "+f"(d[70]), "+f"(d[71])
    : "r"(diag), "r"(b), "n"(OB / 16));
}

#define WEF 2
#define OEF 0
#define PROMO2D CU_TENSOR_MAP_L2_PROMOTION_L2_128B
#define PROMO3D CU_TENSOR_MAP_L2_PROMOTION_L2_256B
#define KVNORM 0
#define PQMAX 4
#define PQLEAD 4
#define PQDT 1400
#define PQT0 2000
#define MAPMODE 3
#define GLAP0 0x53241u
#define EXT0 0
#define EXT2 0
#define EXT3 0
#define PFD 0
#define PFDX 0
#define EARLY_REL 2
#define ST_MODE 0
#define ST_NS 0
#define DELAY_MODE 0
#define PF_Q 2
#define PF_DT_END 200
#define TYPES 0x11110000u
#define N1 0
#define PF_W 0
#define PF_SLEEP 50
#define PF_DT 620
#define PF_T0 3000
#define PF_X 1
#define FAKE_KV 0
#define RED_STEP 0
#define EXP_START 2
#define EXP_END 16

__device__ __forceinline__ void store_acc_T(const float (&d)[72], uint32_t addr) {
  #pragma unroll
  for (int j = 0; j < 18; j += 2)
    stsm4t(addr + j * 1024, pack_bf16(d[4*j], d[4*j+1]), pack_bf16(d[4*j+2], d[4*j+3]),
           pack_bf16(d[4*j+4], d[4*j+5]), pack_bf16(d[4*j+6], d[4*j+7]));
}

template<bool IS_MAX>
__device__ __forceinline__ void warp_col_reduce(const uint32_t (&v)[18], uint32_t (&r3)[3], int lane) {
  #define OP(a, b) (IS_MAX ? max_bf16x2(a, b) : add_bf16x2(a, b))
  const bool b4 = lane & 16, b3 = lane & 8, b2 = lane & 4;
  uint32_t r1[9], r2[5];
  #pragma unroll
  for (int k = 0; k < 9; k++) {
    const uint32_t snd = b4 ? v[k] : v[k+9], kp = b4 ? v[k+9] : v[k];
    r1[k] = OP(kp, __shfl_xor_sync(0xffffffff, snd, 16));
  }
  #pragma unroll
  for (int k = 0; k < 4; k++) {
    const uint32_t snd = b3 ? r1[k] : r1[k+4], kp = b3 ? r1[k+4] : r1[k];
    r2[k] = OP(kp, __shfl_xor_sync(0xffffffff, snd, 8));
  }
  r2[4] = OP(r1[8], __shfl_xor_sync(0xffffffff, r1[8], 8));
  #pragma unroll
  for (int k = 0; k < 2; k++) {
    const uint32_t snd = b2 ? r2[k] : r2[k+2], kp = b2 ? r2[k+2] : r2[k];
    r3[k] = OP(kp, __shfl_xor_sync(0xffffffff, snd, 4));
  }
  r3[2] = OP(r2[4], __shfl_xor_sync(0xffffffff, r2[4], 4));
  #undef OP
}

struct Seg { int isq, head_or_k0, n, np; uint32_t lap, lap2; int lap0; };
__device__ __forceinline__ Seg seg_info(int n, int ty) {
  Seg s;
  const int np = ty ? 2 : 1;
  const int n4 = ty ? 16 + EXT2 : 0, n6 = 16 + (ty ? EXT3 : EXT0);
  s.isq = n <= 3 || n == 5 || (n == 4 && !ty);
  s.head_or_k0 = n == 0 || n == 5 ? 3 : (s.isq ? n - 1 : (n == 4 ? 0 : (n == 6 ? n4 : n4 + n6)));
  s.np = n == 7 ? np : 0;
  s.n = s.isq ? 16 : (n == 4 ? n4 : (n == 6 ? n6 : 64 - n4 - n6 + np));
  const bool g = n == 2 || n == 3 || n == 4 || n == 6;
  s.lap = g ? GLAP0 : 0x12435u;
  s.lap2 = g ? 0x54321u : 0x12435u;
  s.lap0 = n == 0 ? 4 : 0;
  return s;
}

__global__ void __launch_bounds__(384, 1) fused_kernel(const __grid_constant__ Params P) {
  extern __shared__ __align__(1024) char smem_raw[];
  const uint32_t sb = (smem_u32(smem_raw) + 1023u) & ~1023u;
  const uint32_t full0 = sb + OFF_BAR, empty0 = full0 + 48, stg0 = full0 + 96, maxbar = full0 + 104, stgfree = full0 + 112;
  const uint32_t emptyA = full0 + 192;
  const uint32_t ordy = full0 + 144, pdone = full0 + 120;
  const uint32_t kvcnt = full0 + 128;
  const int tid = threadIdx.x;
  const int wg = __shfl_sync(0xffffffff, tid >> 7, 0);
  uint32_t rank; asm volatile("mov.u32 %0, %%cluster_ctarank;" : "=r"(rank));
  int cl;
  { const int c = blockIdx.x >> 1, t = c - 4;
    int set, idx;
    if (c < 4) { set = 1; idx = c; }
    else if (t < 32) { set = 2 * (t & 7); idx = t >> 3; }
    else { set = 2 * (1 + (t - 32) % 7) + 1; idx = (t - 32) / 7; }
    if (MAPMODE == 2) set = (set & 1) ? (set + 2) & 15 : set;
    cl = set * 4 + idx;
    if (MAPMODE == 3) cl = (cl & 7) | (((cl >> 3) & 1) << 5) | ((cl >> 4) << 3);
  }
  const int blk = cl >> 5, b = ((cl >> 3) & 3) * 2 + rank, sub = cl & 7;
  const int ty = (TYPES >> ((cl >> 3) * 4)) & 3, sh = ty == 1;
  uint4* const park = g_park + (cl * 2 + rank) * (4 * (PAIR / 16));

  if (tid == 0) {
    for (int i = 0; i < 6; i++) { mbar_init(full0 + 8*i, 1); mbar_init(empty0 + 8*i, 4); mbar_init(emptyA + 8*i, 2); }
    mbar_init(stg0, 8); mbar_init(maxbar, 8); mbar_init(stgfree, 1); mbar_init(pdone, 1);
    for (int i = 0; i < 4; i++) mbar_init(ordy + 8*i, 1);
    asm volatile("fence.mbarrier_init.release.cluster;" ::: "memory");
  }
  if (tid < 288) asm volatile("st.shared.u32 [%0], %1;" :: "r"(sb + OFF_MAX + tid*4), "r"(0xff800000u) : "memory");
  if (tid == 300) asm volatile("st.shared.u32 [%0], %1;" :: "r"(kvcnt), "r"(0u) : "memory");
  TRINIT();
  __syncthreads();
  cluster_sync();

  if (wg == 2) {
    asm volatile("setmaxnreg.dec.sync.aligned.u32 40;");
    const int warp = __shfl_sync(0xffffffff, (tid >> 5) & 3, 0);
    const int lane = tid & 31;
    #define ACQ(s) do { mbar_wait(ebar + 8*(s), (eph >> (s)) & 1); eph ^= 1u << (s); } while (0)
    const uint32_t ebar = warp == 0 ? emptyA : empty0;
    #define PFT(map, c0, c1) asm volatile(ELECT_BEGIN "@p cp.async.bulk.prefetch.tensor.2d.L2.global.tile [%0, {%1, %2}];\n}\n" :: "l"(map), "r"(c0), "r"(c1) : "memory")
    #define VH(n) ((n) >= 2 && (n) <= 4 ? (n) - 2 : ((n) == 6 ? 3 : -1))
    #define KH(n) ((n) >= 1 && (n) <= 3 ? (n) - 1 : ((n) == (ty == 2 ? 5 : 4) ? 3 : -1))
    if (warp == 0) {
      uint32_t eph = 0x3Fu;
      uint64_t pol; asm volatile("createpolicy.fractional.L2::evict_first.b64 %0, 1.0;" : "=l"(pol));
      if (FAKE_KV || KVNORM) asm volatile("createpolicy.fractional.L2::evict_normal.b64 %0, 1.0;" : "=l"(pol));
      int nkv = 0;
      #define PARK_LOAD(slot, pair) asm volatile(ELECT_BEGIN "@p mbarrier.arrive.expect_tx.shared::cta.b64 _, [%2], %3;\n" \
          "@p cp.async.bulk.shared::cluster.global.mbarrier::complete_tx::bytes [%0], [%1], %3, [%2];\n}\n" \
          :: "r"(sb + (pair) * PAIR), "l"(park + (slot) * (PAIR / 16)), "r"(full0 + 8 * (pair)), "r"(PAIR) : "memory")
      #pragma unroll 1
      for (int n = 1 - sh; n < 8; n++) {
        if (n == 5 && ty != 2) continue;
        Seg sg = seg_info(n, ty);
        const CUtensorMap* map = sg.isq ? &P.x[blk] : &P.os;
        const int row = (sg.isq ? 0 : blk * TOK) + b * SQ, k0 = sg.isq ? 0 : sg.head_or_k0;
        int lp = sg.lap0;
        #pragma unroll 1
        for (int j = 0; j < sg.n; j++) {
          const int s = (sg.lap >> (lp * 4)) & 15;
          const int kk = k0 + j - sg.np;
          if (j < sg.np) {
            if (j == sg.np - 1) mbar_wait(pdone, 0);
            ACQ(s);
            PARK_LOAD(j, s);
          } else {
            if (!sg.isq && (kk & 15) == 0) mbar_wait(ordy + 8 * (kk >> 4), 0);
            ACQ(s);
            if (OEF && !sg.isq) tma2d(sb + s * PAIR, map, kk * 64, row, full0 + 8*s, 18432 + 16384, pol);
            else tma2d(sb + s * PAIR, map, kk * 64, row, full0 + 8*s, 18432 + 16384);
          }
          if (++lp == 5) { lp = 0; if (j >= sg.n - 12) sg.lap = sg.lap2; }
        }
        const int vh = VH(n), kh = KH(n);
        #pragma unroll 1
        for (int q = (vh < 0 ? 4 : 0); q < (kh < 0 ? 4 : 8); q++) {
          if (sh && n == 4 && q == 4) {
            ACQ(5);
            PARK_LOAD(2, 5);
          }
          const int s = (0x32432432u >> (q * 4)) & 15;
          const int head = (q < 4 ? vh : kh) * 8 + sub;
          ACQ(s);
          tma3d_hint(sb + s * PAIR, q < 4 ? &P.v[blk] : &P.k[blk], (FAKE_KV ? sub : b * 32 + head) * 512 + ((q < 4 ? q : q + 1) & 3) * 128, full0 + 8*s, pol, 32768);
          nkv++;
          asm volatile("st.volatile.shared.u32 [%0], %1;" :: "r"(kvcnt), "r"(nkv) : "memory");
        }
      }
    } else if (warp == 1) {
      uint64_t wpol; asm volatile("createpolicy.fractional.L2::evict_first.b64 %0, 1.0;" : "=l"(wpol));
      uint32_t eph = 0x3Fu;
      #pragma unroll 1
      for (int n = 1 - sh; n < 8; n++) {
        if (n == 5 && ty != 2) continue;
        Seg sg = seg_info(n, ty);
        const CUtensorMap* map = sg.isq ? &P.wq[blk] : &P.wo[blk];
        const int col = (sg.isq ? sg.head_or_k0 * 8 + sub : sub) * 128 + rank * 64, k0 = sg.isq ? 0 : sg.head_or_k0;
        int lp = sg.lap0;
        #pragma unroll 1
        for (int j = 0; j < sg.n; j++) {
          const int s = (sg.lap >> (lp * 4)) & 15;
          if (j >= sg.np) {
            ACQ(s);
            if (WEF == 1 || (WEF == 2 && sg.isq) || (WEF == 3 && n < 7)) tma2d_mc(sb + s * PAIR + SLOT + rank * 8192, map, col, (k0 + j - sg.np) * 64, full0 + 8*s, wpol);
            else tma2d_mc(sb + s * PAIR + SLOT + rank * 8192, map, col, (k0 + j - sg.np) * 64, full0 + 8*s);
          }
          if (++lp == 5) { lp = 0; if (j >= sg.n - 12) sg.lap = sg.lap2; }
        }
      }
    } else if (warp == 2) {
      uint32_t ph = 0;
      #define ST_GAP() do { if (ST_MODE == 1) { asm volatile("cp.async.bulk.commit_group;" ::: "memory"); asm volatile("cp.async.bulk.wait_group.read 0;" ::: "memory"); } else if (ST_NS) __nanosleep(ST_NS); } while (0)
      #define PARK_STORE(slot, pair) do { if (lane == 0) { mbar_wait(stg0, ph); \
          _Pragma("unroll 1") for (int pc = 0; pc < 12; pc++) { \
            asm volatile("cp.async.bulk.global.shared::cta.bulk_group [%0], [%1], %2;" :: "l"(park + (slot) * (PAIR / 16) + pc * 192), "r"(sb + (pair) * PAIR + pc * 3072), "r"(3072) : "memory"); \
            ST_GAP(); } \
          asm volatile("cp.async.bulk.commit_group;" ::: "memory"); \
          asm volatile("cp.async.bulk.wait_group.read 0;" ::: "memory"); \
          if (pair) { mbar_arrive_cta(emptyA + 40, rank, 2); if (ty == 2 && (slot) == 0) { mbar_arrive_cta(empty0 + 40, 0, 2); mbar_arrive_cta(empty0 + 40, 1, 2); } } else mbar_arrive(stgfree); } \
          ph ^= 1; __syncwarp(); } while (0)
      if (sh) PARK_STORE(2, 0);
      #pragma unroll 1
      for (int n = 0; n < 4; n++) {
        if (n == 3 || (n == 2 && ty)) PARK_STORE(ty ? n - 2 : 0, 5);
        bar_sync<4, 288>();
        #pragma unroll
        for (int r = 0; r < 3; r++) {
          const int idx = r * 32 + lane;
          if (idx < 72) {
            float s0 = 0.f, s1 = 0.f;
            #pragma unroll
            for (int ww = 0; ww < 8; ww++) {
              uint32_t v; asm volatile("ld.shared.u32 %0, [%1];" : "=r"(v) : "r"(sb + OFF_SUM + ww * 288 + idx * 4));
              s0 += bf_lo(v); s1 += bf_hi(v);
            }
            asm volatile("st.shared.v2.f32 [%0], {%1, %2};" :: "r"(sb + OFF_INV + idx * 8), "f"(__fdividef(1.f, s0)), "f"(__fdividef(1.f, s1)) : "memory");
          }
        }
        bar_arrive<7, 160>();
        bar_arrive<8, 160>();
        if (lane == 0) {
          if (n == 3) { asm volatile("cp.async.bulk.wait_group 0;" ::: "memory"); asm volatile("fence.proxy.async.global;" ::: "memory"); mbar_arrive(pdone); }
          mbar_wait(stg0, ph); EV(n * 6);
          #pragma unroll 1
          for (int pc = 0; pc < 12; pc++) {
            tma2d_store(&P.oss, (n * 8 + sub) * 128 + (pc & 1) * 64, blk * TOK + b * SQ + (pc >> 1) * 24, sb + (pc & 1) * SLOT + (pc >> 1) * 3072);
            ST_GAP();
          }
          asm volatile("cp.async.bulk.commit_group;" ::: "memory");
          asm volatile("cp.async.bulk.wait_group.read 0;" ::: "memory");
          mbar_arrive(stgfree); EV(n * 6 + 1);
          asm volatile("cp.async.bulk.wait_group 0;" ::: "memory"); EV(n * 6 + 2);
          asm volatile("fence.proxy.async.global;" ::: "memory");
          asm volatile("red.release.gpu.global.add.u32 [%0], %1;" :: "l"(&g_cnt[(blk * 8 + b) * 4 + n]), "r"(1u) : "memory"); EV(n * 6 + 3);
        }
        ph ^= 1;
        __syncwarp();
      }
      if (lane == 0) {
        mbar_wait(stg0, ph);
        tma2d_store(&P.out, blk * 1024 + sub * 128, b * SQ, sb);
        tma2d_store(&P.out, blk * 1024 + sub * 128 + 64, b * SQ, sb + SLOT);
        asm volatile("cp.async.bulk.commit_group;" ::: "memory");
        asm volatile("cp.async.bulk.wait_group.read 0;" ::: "memory");
      }
    } else {
      unsigned int epoch;
      asm volatile("ld.relaxed.gpu.global.u32 %0, [%1];" : "=r"(epoch) : "l"(&g_done) : "memory");
      const unsigned int target = 8u * ((epoch >> 7) + 1);
      if (PQMAX) {
        const size_t bh0 = (size_t)(b * 32 + sub) * (512 * 256) + lane * 256;
        uint32_t v0 = 0, v1 = 0;
        uint32_t tnext = (uint32_t)clock64() + PQT0;
        int q = 0;
        #pragma unroll 1
        for (int spin = 0; spin < 1000000 && q < 2 * PQMAX; spin++) {
          int cnt; asm volatile("ld.volatile.shared.u32 %0, [%1];" : "=r"(cnt) : "r"(kvcnt) : "memory");
          if (q < cnt * 2) q = cnt * 2;
          const uint32_t now = (uint32_t)clock64();
          if ((int)(now - tnext) >= 0 && q < (cnt + PQLEAD) * 2 && q < 2 * PQMAX) {
            const int pr = q >> 1;
            const char* a = ((pr & 4) ? P.vptr[blk] : P.kptr[blk]) + bh0 + (size_t)(pr >> 3) * (8 * 512 * 256) + (((pr & 4) ? pr : pr + 1) & 3) * 32768 + (q & 1) * 16384;
            asm volatile("st.volatile.shared.u32 [%0], %1;" :: "r"(kvcnt + 8), "r"(v0 ^ v1) : "memory");
            asm volatile("ld.global.L2::256B.u32 %0, [%1];" : "=r"(v0) : "l"(a) : "memory");
            asm volatile("ld.global.L2::256B.u32 %0, [%1];" : "=r"(v1) : "l"(a + 8192) : "memory");
            q++; tnext = now + PQDT;
          } else __nanosleep(50);
        }
        asm volatile("st.volatile.shared.u32 [%0], %1;" :: "r"(kvcnt + 8), "r"(v0 ^ v1) : "memory");
      }
      int nrdy = 0;
      #pragma unroll 1
      for (int spin = 0; spin < 1000000 && nrdy < 4; spin++) {
        int cnt; asm volatile("ld.volatile.shared.u32 %0, [%1];" : "=r"(cnt) : "r"(kvcnt) : "memory");
        if (cnt >= nrdy * 8 + 8) {
          unsigned int c; asm volatile("ld.acquire.gpu.global.u32 %0, [%1];" : "=r"(c) : "l"(&g_cnt[(blk * 8 + b) * 4 + nrdy]) : "memory");
          if ((int)(c - target) >= 0) {
            asm volatile("fence.proxy.async.global;" ::: "memory");
            __syncwarp();
            if (lane == 0) mbar_arrive(ordy + 8 * nrdy);
            nrdy++;
          }
        }
        __nanosleep(100);
      }
      if (lane == 0) atomicAdd(&g_done, 1u);
    }
    __syncwarp();
    cluster_sync();
  } else {
    asm volatile("setmaxnreg.inc.sync.aligned.u32 232;");
    const int w = wg;
    int t128 = tid & 127;
    asm volatile("" : "+r"(t128));
    #define lane (t128 & 31)
    #define warp (t128 >> 5)
    const uint32_t st_base = sb + w * SLOT + (uint32_t)(((lane >> 4) * 8 + (lane & 7)) * 128 + (((2 * warp + ((lane >> 3) & 1)) ^ (lane & 7)) << 4));
    const uint32_t d0 = ((sb & 0x3FFFF) >> 4) | (64u << 16);
    const uint32_t d0w = d0 + w * 512, d0v = d0 + w * 1024;
    uint32_t rel_addr; asm("mapa.shared::cluster.u32 %0, %1, %2;" : "=r"(rel_addr) : "r"(t128 == 0 ? emptyA : empty0), "r"(t128 == 0 ? rank : (uint32_t)(t128 & 1)));
    #define WAITF(s, flip) mbar_wait(full0 + 8*(s), ((fph >> (s)) & 1) ^ (flip))
    #define RELX(s, all) asm volatile("{\n.reg .pred p;\nsetp.lt.u32 p, %1, %2;\n@p mbarrier.arrive.relaxed.cluster.shared::cluster.b64 _, [%0];\n}\n" :: "r"(rel_addr + 8*(s)), "r"(t128), "r"((all) ? 3 : 1) : "memory")
    #define REL(s) RELX(s, true)
    #define STG_ARRIVE() do { fence_async_smem(); __syncwarp(); if (lane == 0) mbar_arrive(stg0); } while (0)
    #define STG_FREE() do { mbar_wait(stgfree, sfp); sfp ^= 1; } while (0)
    #define TURN_WAIT() do { if (w) bar_sync<6, 256>(); else bar_sync<5, 256>(); } while (0)
    #define TURN_PASS() do { if (w) bar_arrive<5, 256>(); else bar_arrive<6, 256>(); } while (0)
    #define GMMA(acc, da, db, O, first) do { if (!(first)) fence_regs(acc); wg_fence(); \
        if (first) mma_init<1, (O) + SLOT, (O)>(acc, da, db); else mma<1, (O) + SLOT, (O)>(acc, da, db); \
        mma<1, (O) + SLOT + 2048, (O) + 32>(acc, da, db); mma<1, (O) + SLOT + 4096, (O) + 64>(acc, da, db); \
        mma<1, (O) + SLOT + 6144, (O) + 96>(acc, da, db); wg_commit(); } while (0)
    #define O_STSM() do { _Pragma("unroll") for (int c_ = 0; c_ < 9; c_++) \
        stsm4t(st_base + c_ * 2048, ok[4*c_], ok[4*c_+1], ok[4*c_+2], ok[4*c_+3]); } while (0)
    #define O_STORE() do { O_STSM(); STG_ARRIVE(); } while (0)
    #define SMMA(p) do { \
        mma_init<0, (p) * PAIR, 5 * PAIR>(s, d0w, d0);     mma<0, (p) * PAIR + 32, 5 * PAIR + 32>(s, d0w, d0); \
        mma<0, (p) * PAIR + 64, 5 * PAIR + 64>(s, d0w, d0); mma<0, (p) * PAIR + 96, 5 * PAIR + 96>(s, d0w, d0); \
        mma<0, (p) * PAIR + 16384, 5 * PAIR + SLOT>(s, d0w, d0);           mma<0, (p) * PAIR + 16384 + 32, 5 * PAIR + SLOT + 32>(s, d0w, d0); \
        mma<0, (p) * PAIR + 16384 + 64, 5 * PAIR + SLOT + 64>(s, d0w, d0); mma<0, (p) * PAIR + 16384 + 96, 5 * PAIR + SLOT + 96>(s, d0w, d0); } while (0)
    const float cs = 0.08838834764831845f * 1.4426950408889634f;
    uint32_t fph = 0, sfp = 0;
    uint32_t ok[36];
    #pragma unroll
    for (int i = 0; i < 36; i++) ok[i] = 0;
    TR(0); TRG(0);
    #pragma unroll 1
    for (int h = -sh; h < 5; h++) {
      const bool hasx = h <= 0 || h == 4 || (h == 3 && ty == 2);
      const int tb = 2 + (h < 0 ? 0 : h) * 11; (void)tb;
      if (hasx) {
        const Seg sg = seg_info(h <= 0 ? h + 1 : 2 * h - 1, ty);
        float a0[72];
        #pragma unroll
        for (int i = 0; i < 72; i++) a0[i] = 0.f;
        if (h > 0 && !w) bar_sync<5, 256>();
        int lp = sg.lap0, sprev = 0, j0 = 0;
        if (h == 4) {
          const uint32_t dg = (lane >> 3) == (lane & 3) ? ((lane & 4) ? 0x3f800000u : 0x00003f80u) : 0u;
          const uint32_t db = d0 + w * (SLOT / 16);
          const uint32_t g0 = warp == 0 ? dg : 0u, g1 = warp == 1 ? dg : 0u, g2 = warp == 2 ? dg : 0u, g3 = warp == 3 ? dg : 0u;
          #define FOLD(p) do { WAITF(p, 0); fence_regs(a0); wg_fence(); \
              mma_rs<(p) * PAIR>(a0, g0, db); mma_rs<(p) * PAIR + 32>(a0, g1, db); mma_rs<(p) * PAIR + 64>(a0, g2, db); mma_rs<(p) * PAIR + 96>(a0, g3, db); \
              wg_commit(); } while (0)
          O_STSM(); FOLD(5); STG_ARRIVE(); wg_wait<0>(); fence_regs(a0); REL(5);
          if (ty) { FOLD(3); wg_wait<0>(); fence_regs(a0); REL(3); }
          fph ^= ty ? 0x28u : 0x20u; lp = sg.np; j0 = sg.np;
        }
        #pragma unroll 1
        for (int j = j0; j < sg.n; j++) {
          const int s = (sg.lap >> (lp * 4)) & 15;
          WAITF(s, 0); fph ^= 1u << s;
          TRS((h < 0 ? 0 : (h == 0 ? 1 : h - 1)) * 24 + j);
          const uint32_t off = s * (PAIR / 16);
          GMMA(a0, d0w + off, d0 + off, 0, false);
          if (h == 3 && j == 0) O_STSM();
          if (h == 3 && j == 1) STG_ARRIVE();
          wg_wait<1>();
          if (j > j0) RELX(sprev, !(h >= 0 && j > sg.n - 5 && sprev >= 2 && sprev <= 4));
          sprev = s;
          if (++lp == 5) lp = 0;
        }
        const bool toq = h == 0 || h == 3;
        if (h == 4) STG_FREE();
        wg_wait<0>();
        fence_regs(a0);
        TR(tb);
        if (toq) bar_sync<3, 256>(); else REL(sprev);
        const float f = sg.isq ? cs : 1.f;
        #pragma unroll
        for (int i = 0; i < 72; i++) a0[i] *= f;
        store_acc_T(a0, st_base + (toq ? 5 * PAIR : 0));
        fence_async_smem();
        if (!toq) { __syncwarp(); if (lane == 0) mbar_arrive(stg0); }
        if (h >= 0 && h < 4 && w) bar_arrive<5, 256>();
      }
      if (h < 0 || h == 4) continue;
      const uint32_t hodd = h & 1;
      const bool nextx = h == 3 || (h == 2 && ty == 2), gq = h < 2 || (h == 2 && !ty);
      const uint32_t ma = sb + OFF_MAX + hodd * 576 + (lane & 3) * 144;
      uint32_t sp[3][36];
      uint32_t l2[18];
      uint32_t mx[18];
      TR(tb + 1);
      #pragma unroll
      for (int i = 0; i < 4; i++) {
        constexpr int KSL[4] = {3, 4, 2, 3};
        WAITF(KSL[i], i == 3);
        float s[72];
        TURN_WAIT();
        if (h == 1) TRS(128 + i);
        wg_fence();
        if (i == 0 || i == 3) { SMMA(3); } else if (i == 1) { SMMA(4); } else { SMMA(2); }
        wg_commit();
        if (i < 3 || !w) TURN_PASS();
        if (i == 0 && !hasx) O_STORE();
        if (i == 3 && h + sh > 0) STG_FREE();
        wg_wait<0>();
        fence_regs(s);
        RELX(KSL[i], i > 0);
        if (i < 3) {
          #pragma unroll
          for (int j = 0; j < 18; j++) {
            sp[i][2*j] = pack_bf16(s[4*j], s[4*j+1]);
            sp[i][2*j+1] = pack_bf16(s[4*j+2], s[4*j+3]);
            const uint32_t m2 = max_bf16x2(sp[i][2*j], sp[i][2*j+1]);
            mx[j] = i ? max_bf16x2(mx[j], m2) : m2;
            asm volatile("" : "+r"(sp[i][2*j]), "+r"(sp[i][2*j+1]), "+r"(mx[j]) :: "memory");
          }
        } else {
          REL(5);
          #pragma unroll
          for (int c = 0; c < 9; c++) {
            const uint32_t k0 = pack_bf16(s[8*c], s[8*c+1]), k1 = pack_bf16(s[8*c+2], s[8*c+3]);
            const uint32_t k2 = pack_bf16(s[8*c+4], s[8*c+5]), k3 = pack_bf16(s[8*c+6], s[8*c+7]);
            stsm4t(st_base + c * 2048, k0, k1, k2, k3);
            mx[2*c] = max_bf16x2(mx[2*c], max_bf16x2(k0, k1));
            mx[2*c+1] = max_bf16x2(mx[2*c+1], max_bf16x2(k2, k3));
            asm volatile("" : "+r"(mx[2*c]), "+r"(mx[2*c+1]) :: "memory");
          }
        }
      }
      fph ^= 0x14u;
      TR(tb + 2);
      #define STORE_P(i) do { _Pragma("unroll") for (int c_ = 0; c_ < 9; c_++) \
          stsm4t(st_base + ((i) & 1) * PAIR + c_ * 2048, sp[(i)-1][4*c_], sp[(i)-1][4*c_+1], sp[(i)-1][4*c_+2], sp[(i)-1][4*c_+3]); } while (0)
      {
        float a0[72];
        #define U0(j) ((j) <= EXP_START ? 0 : ((j) >= EXP_END ? 27 : (((j) - EXP_START) * 27) / (EXP_END - EXP_START)))
        uint32_t mm[2][2], pk[2][4];
        float4 mr;
        uint16_t eh[3][8];
        #define GP(j) ((j) < 0 ? 1 : ((j) < 5 ? (int)((GLAP0 >> (((j) & 7) * 4)) & 15) : 1 + (j) % 5))
        #define GSTEP(j) do { \
          constexpr int p_ = GP(j) - 1; \
          WAITF(1 + p_, ((j) / 5) & 1); \
          if (h == 1) TRS(132 + (j)); \
          if ((EARLY_REL & 2) && (j) > 0) { wg_wait<0>(); if ((j) < 15) RELX(GP((j) - 1), (j) < 12); } \
          if ((j) == EXP_START - 1) mbar_wait(maxbar, hodd); \
          GMEM(j); \
          GMMA(a0, d0w, d0, (1 + p_) * PAIR, (j) == 0); \
          if ((j) == RED_STEP) { \
            uint32_t r3[3]; warp_col_reduce<true>(mx, r3, lane); \
            const int jb = (lane & 16) ? 9 : 0, j0 = jb + ((lane & 8) ? 4 : 0) + ((lane & 4) ? 2 : 0); \
            red_max_f32(ma + j0 * 8, bf_lo(r3[0]), true);      red_max_f32(ma + j0 * 8 + 4, bf_hi(r3[0]), true); \
            red_max_f32(ma + j0 * 8 + 8, bf_lo(r3[1]), true);  red_max_f32(ma + j0 * 8 + 12, bf_hi(r3[1]), true); \
            red_max_f32(ma + (jb + 8) * 8, bf_lo(r3[2]), !(lane & 12)); red_max_f32(ma + (jb + 8) * 8 + 4, bf_hi(r3[2]), !(lane & 12)); \
            __syncwarp(); if (lane == 0) mbar_arrive(maxbar); TR(tb + 3); } \
          GEXP(j); \
          if (!(EARLY_REL & 2) && (j) > 0) { wg_wait<1>(); if ((j) < 15) RELX(GP((j) - 1), (j) < 12); } } while (0)
        #define GMEM(j) do { \
          _Pragma("unroll") for (int u = U0(j); u < U0((j) + 1); u++) if (u % 3 == 0) { \
            mm[(u / 3) & 1][0] = __byte_perm(__float_as_uint(mr.x), __float_as_uint(mr.y), 0x7632); \
            mm[(u / 3) & 1][1] = __byte_perm(__float_as_uint(mr.z), __float_as_uint(mr.w), 0x7632); } \
          _Pragma("unroll") for (int u = U0((j) - 1); u < U0(j); u++) if (u % 3 == 0) { \
            const int c = u / 3; uint16_t (&e)[8] = eh[u - U0((j) - 1)]; \
            const uint32_t k0 = pack_halves(e[0], e[1]), k1 = pack_halves(e[2], e[3]), k2 = pack_halves(e[4], e[5]), k3 = pack_halves(e[6], e[7]); \
            stsm4t(st_base + c * 2048, k0, k1, k2, k3); \
            l2[2*c] = add_bf16x2(k0, k1); l2[2*c+1] = add_bf16x2(k2, k3); asm volatile("" : "+r"(l2[2*c]), "+r"(l2[2*c+1])); } \
          _Pragma("unroll") for (int u = U0((j) + 1); u < U0((j) + 2); u++) if (u % 3 == 0) { \
            const int c = u / 3; \
            mr = lds128(ma + c * 16); \
            ldsm4t(st_base + c * 2048, pk[c & 1][0], pk[c & 1][1], pk[c & 1][2], pk[c & 1][3]); \
          } } while (0)
        #define GEXP(j) do { \
          _Pragma("unroll") for (int u = U0((j) - 1); u < U0(j); u++) if (u % 3) { \
            const int c = u / 3, t = u % 3; uint16_t (&e)[8] = eh[u - U0((j) - 1)]; \
            uint32_t (&q)[36] = sp[t ? t - 1 : 0]; \
            q[4*c] = pack_halves_pin(e[0], e[1]); q[4*c+1] = pack_halves_pin(e[2], e[3]); \
            q[4*c+2] = pack_halves_pin(e[4], e[5]); q[4*c+3] = pack_halves_pin(e[6], e[7]); \
            l2[2*c] = add_bf16x2(l2[2*c], add_bf16x2(q[4*c], q[4*c+1])); l2[2*c+1] = add_bf16x2(l2[2*c+1], add_bf16x2(q[4*c+2], q[4*c+3])); \
            asm volatile("" : "+r"(l2[2*c]), "+r"(l2[2*c+1])); \
          } \
          _Pragma("unroll") for (int u = U0(j); u < U0((j) + 1); u++) { \
            const int c = u / 3, t = u % 3; uint16_t (&e)[8] = eh[u - U0(j)]; \
            const uint32_t* q = t ? &sp[t ? t - 1 : 0][4*c] : pk[c & 1]; \
            ex2_halves(sub_bf16x2(q[0], mm[c & 1][0]), e[0], e[1]); ex2_halves(sub_bf16x2(q[1], mm[c & 1][0]), e[2], e[3]); \
            ex2_halves(sub_bf16x2(q[2], mm[c & 1][1]), e[4], e[5]); ex2_halves(sub_bf16x2(q[3], mm[c & 1][1]), e[6], e[7]); \
            if (t == 2) { \
              sp[2][4*c] = sub_bf16x2(sp[2][4*c], mm[c & 1][0]); sp[2][4*c+1] = sub_bf16x2(sp[2][4*c+1], mm[c & 1][0]); \
              sp[2][4*c+2] = sub_bf16x2(sp[2][4*c+2], mm[c & 1][1]); sp[2][4*c+3] = sub_bf16x2(sp[2][4*c+3], mm[c & 1][1]); \
              asm volatile("" : "+r"(sp[2][4*c]), "+r"(sp[2][4*c+1]), "+r"(sp[2][4*c+2]), "+r"(sp[2][4*c+3])); } \
          } } while (0)
        GSTEP(0);
        {
          const int ext = gq ? 0 : (h == 2 ? EXT2 : (ty ? EXT3 : EXT0));
          int lp = 1, sprev = 1;
          if (ext) fph ^= 2u;
          #pragma unroll 1
          for (int e = 0; e < ext; e++) {
            const int s = (GLAP0 >> (lp * 4)) & 15;
            WAITF(s, 0); fph ^= 1u << s;
            const uint32_t off = s * (PAIR / 16);
            GMMA(a0, d0w + off, d0 + off, 0, false);
            wg_wait<1>();
            REL(sprev);
            sprev = s;
            if (++lp == 5) lp = 0;
          }
          if (ext) fph ^= 2u;
        }
        GSTEP(1); GSTEP(2); GSTEP(3); GSTEP(4); GSTEP(5); GSTEP(6); GSTEP(7); GSTEP(8); GSTEP(9);
        GSTEP(10); GSTEP(11); GSTEP(12); GSTEP(13); GSTEP(14); GSTEP(15);
        fph ^= 0x3Cu;
        WAITF(2, 0);
        GMEM(16); GEXP(16);
        fence_async_smem();
        bar_sync<3, 256>();
        wg_wait<0>();
        fence_regs(a0);
        if (w) bar_arrive<10, 256>();
        TR(tb + 4);
        if (gq) {
          #pragma unroll
          for (int i = 0; i < 72; i++) a0[i] *= cs;
        }
        store_acc_T(a0, st_base + 5 * PAIR);
        TR(tb + 5);
      }
      float o[72];
      #define PVSTEP(i) do { \
        constexpr int v_ = (i) == 3 ? 2 : 2 + (i), pb_ = ((i) & 1) * PAIR; \
        if ((i) > 0) { \
          if (!w) { bar_sync<9 + ((i) & 1), 256>(); STORE_P((i) ? (i) : 1); } \
          if ((i) == 2) { \
            uint32_t r3[3]; \
            warp_col_reduce<false>(l2, r3, lane); \
            const int jb = (lane & 16) ? 9 : 0, j0 = jb + ((lane & 8) ? 4 : 0) + ((lane & 4) ? 2 : 0); \
            const uint32_t sa = sb + OFF_SUM + (w * 4 + warp) * 288 + (lane & 3) * 72; \
            asm volatile("st.shared.u32 [%0], %1;" :: "r"(sa + j0 * 4), "r"(r3[0]) : "memory"); \
            asm volatile("st.shared.u32 [%0], %1;" :: "r"(sa + j0 * 4 + 4), "r"(r3[1]) : "memory"); \
            asm volatile("st.shared.u32 [%0], %1;" :: "r"(sa + (jb + 8) * 4), "r"(r3[2]) : "memory"); \
            if (t128 < 72) asm volatile("st.shared.u32 [%0], %1;" :: "r"(sb + OFF_MAX + (hodd ^ 1) * 576 + w * 288 + t128 * 4), "r"(0xff800000u) : "memory"); \
            bar_arrive<4, 288>(); } \
          WAITF(v_, (i) == 3); \
          if (!w) fence_async_smem(); \
          if ((i) == 1 && !gq) { __syncwarp(); if (lane == 0) mbar_arrive(stg0); }     \
          wg_wait<0>(); \
          RELX(1 + (i), (i) > 1 && nextx && !(h == 3 && ty && (i) == 2)); \
        } \
        if (!w) { if ((i) > 0) bar_sync<5, 256>(); } else { \
          if ((i) > 0 && (i) < 3) bar_arrive<10 - ((i) & 1), 256>(); \
          bar_sync<6, 256>(); \
          if ((i) < 3) STORE_P((i) < 3 ? (i) + 1 : 1); \
        } \
        if (h == 1) TRS(148 + (i)); if (h == 0 && (i) == 3) TRS(127); \
        if ((i) > 0) fence_regs(o); \
        wg_fence(); \
        if ((i) == 0) mma_init<1, v_ * PAIR, pb_>(o, d0v, d0); else mma<1, v_ * PAIR, pb_>(o, d0v, d0); \
        mma<1, v_ * PAIR + 2048, pb_ + 32>(o, d0v, d0); mma<1, v_ * PAIR + 4096, pb_ + 64>(o, d0v, d0); mma<1, v_ * PAIR + 6144, pb_ + 96>(o, d0v, d0); \
        mma<1, v_ * PAIR + 8192, pb_ + SLOT>(o, d0v, d0);       mma<1, v_ * PAIR + 10240, pb_ + SLOT + 32>(o, d0v, d0); \
        mma<1, v_ * PAIR + 12288, pb_ + SLOT + 64>(o, d0v, d0); mma<1, v_ * PAIR + 14336, pb_ + SLOT + 96>(o, d0v, d0); \
        wg_commit(); \
        if (!w) bar_arrive<6, 256>(); \
        if ((i) < 2) { sched_sep(P.zero); \
          _Pragma("unroll") for (int r_ = (i) * 18; r_ < (i) * 18 + 18; r_ += 2) { \
            sp[2][r_] = ex2_bf16x2(sp[2][r_]); sp[2][r_+1] = ex2_bf16x2(sp[2][r_+1]); \
            l2[r_ / 2] = add_bf16x2(l2[r_ / 2], add_bf16x2(sp[2][r_], sp[2][r_+1])); \
            asm volatile("" : "+r"(sp[2][r_]), "+r"(sp[2][r_+1]), "+r"(l2[r_ / 2])); } \
          sched_sep(P.zero); } \
        if (w) { if ((i) < 3) fence_async_smem(); bar_arrive<5, 256>(); } \
        TR(tb + 6 + (i)); } while (0)
      PVSTEP(0);
      PVSTEP(1);
      PVSTEP(2);
      PVSTEP(3);
      fph ^= 0x18u;
      {
        if (sh && h == 2) { WAITF(5, 0); fph ^= 0x20u; }
        if (w) bar_sync<8, 160>(); else bar_sync<7, 160>();
        float4 iv[9];
        #pragma unroll
        for (int j = 0; j < 9; j++) iv[j] = lds128(sb + OFF_INV + (lane & 3) * 144 + j * 16);
        wg_wait<0>();
        fence_regs(o);
        RELX(2, nextx); REL(1);
        #pragma unroll
        for (int j = 0; j < 9; j++) {
          ok[4*j]   = pack_bf16(o[8*j] * iv[j].x, o[8*j+1] * iv[j].y);   ok[4*j+1] = pack_bf16(o[8*j+2] * iv[j].x, o[8*j+3] * iv[j].y);
          ok[4*j+2] = pack_bf16(o[8*j+4] * iv[j].z, o[8*j+5] * iv[j].w); ok[4*j+3] = pack_bf16(o[8*j+6] * iv[j].z, o[8*j+7] * iv[j].w);
        }
      }
      TR(tb + 10); if (tid == 128) EV(h * 6 + 5);
    }
    TR(56);
    cluster_sync();
    TR(57); TRG(1); TRDUMP(); TRSDUMP();
    #undef lane
    #undef warp
  }
}

typedef CUresult (*PFN_enc)(CUtensorMap*, CUtensorMapDataType, cuuint32_t, void*, const cuuint64_t*, const cuuint64_t*,
                            const cuuint32_t*, const cuuint32_t*, CUtensorMapInterleave, CUtensorMapSwizzle,
                            CUtensorMapL2promotion, CUtensorMapFloatOOBfill);

void enc2d(PFN_enc enc, CUtensorMap* m, const void* p, uint64_t cols, uint64_t rows, uint32_t box_rows) {
  cuuint64_t dims[2] = {cols, rows}; cuuint64_t st[1] = {cols * 2};
  cuuint32_t box[2] = {64, box_rows}; cuuint32_t es[2] = {1, 1};
  enc(m, CU_TENSOR_MAP_DATA_TYPE_BFLOAT16, 2, (void*)p, dims, st, box, es, CU_TENSOR_MAP_INTERLEAVE_NONE,
      CU_TENSOR_MAP_SWIZZLE_128B, PROMO2D, CU_TENSOR_MAP_FLOAT_OOB_FILL_NONE);
}
void enc3d(PFN_enc enc, CUtensorMap* m, const void* p, uint64_t cols, uint64_t rows) {
  cuuint64_t dims[3] = {64, rows, cols / 64}; cuuint64_t st[2] = {cols * 2, 128};
  cuuint32_t box[3] = {64, 128, 2}; cuuint32_t es[3] = {1, 1, 1};
  enc(m, CU_TENSOR_MAP_DATA_TYPE_BFLOAT16, 3, (void*)p, dims, st, box, es, CU_TENSOR_MAP_INTERLEAVE_NONE,
      CU_TENSOR_MAP_SWIZZLE_128B, PROMO3D, CU_TENSOR_MAP_FLOAT_OOB_FILL_NONE);
}

}

extern "C" void kernel_launch(void* const* d_in, const int* in_sizes, int n_in, void* d_out, int out_size) {
  (void)in_sizes; (void)n_in; (void)out_size;
  void* fn = nullptr; cudaDriverEntryPointQueryResult q;
  cudaGetDriverEntryPoint("cuTensorMapEncodeTiled", &fn, cudaEnableDefault, &q);
  PFN_enc enc = (PFN_enc)fn;
  void* oscr = nullptr; cudaGetSymbolAddress(&oscr, g_oscr);
  Params P;
  for (int i = 0; i < 2; i++) {
    enc2d(enc, &P.x[i], d_in[5*i + 0], 1024, TOK, SQ);
    enc3d(enc, &P.k[i], d_in[5*i + 1], 128, 8 * 32 * 512);
    enc3d(enc, &P.v[i], d_in[5*i + 2], 128, 8 * 32 * 512);
    enc2d(enc, &P.wq[i], d_in[5*i + 3], 4096, 1024, 64);
    enc2d(enc, &P.wo[i], d_in[5*i + 4], 1024, 4096, 64);
    P.kptr[i] = (const char*)d_in[5*i + 1]; P.vptr[i] = (const char*)d_in[5*i + 2];
    P.xptr[i] = (const char*)d_in[5*i + 0];
    P.wqptr[i] = (const char*)d_in[5*i + 3]; P.woptr[i] = (const char*)d_in[5*i + 4];
  }
  P.zero = 0;
  enc2d(enc, &P.os, oscr, 4096, 2 * TOK, SQ);
  enc2d(enc, &P.oss, oscr, 4096, 2 * TOK, 24);
  enc2d(enc, &P.out, d_out, 2048, TOK, SQ);
  cudaFuncSetAttribute(fused_kernel, cudaFuncAttributeMaxDynamicSharedMemorySize, SMEM_BYTES);
  cudaLaunchConfig_t cfg = {};
  cfg.gridDim = dim3(NCTA); cfg.blockDim = dim3(384); cfg.dynamicSmemBytes = SMEM_BYTES; cfg.stream = cudaStreamPerThread;
  cudaLaunchAttribute at[1];
  at[0].id = cudaLaunchAttributeClusterDimension; at[0].val.clusterDim.x = 2; at[0].val.clusterDim.y = 1; at[0].val.clusterDim.z = 1;
  cfg.attrs = at; cfg.numAttrs = 1;
  cudaLaunchKernelEx(&cfg, fused_kernel, P);
}
```

```cpp
#include <cuda_runtime.h>
#include <cuda.h>
#include <cuda_bf16.h>
#include <stdint.h>

namespace {

constexpr int SQ = 144;
constexpr int TOK = 1152;
constexpr int SLOT = 18432;
constexpr int PAIR = 2 * SLOT;
constexpr int OFF_BAR = 6 * PAIR;
constexpr int OFF_MAX = OFF_BAR + 256;
constexpr int OFF_SUM = OFF_MAX + 2 * 576;
constexpr int OFF_INV = OFF_SUM + 8 * 288;
constexpr int SMEM_BYTES = OFF_INV + 576 + 1024;
constexpr int NCTA = 128;

struct alignas(64) Params {
  CUtensorMap x[2], wq[2], k[2], v[2], wo[2], os, oss, out;
  const char* kptr[2];
  uint32_t zero;
};

__device__ __nv_bfloat16 g_oscr[2 * TOK * 4096];
__device__ uint4 g_park[NCTA * 2 * (PAIR / 16)];
__device__ unsigned int g_cnt[64];
__device__ unsigned int g_done;

__device__ __forceinline__ uint32_t smem_u32(const void* p) { return (uint32_t)__cvta_generic_to_shared(p); }
__device__ __forceinline__ void mbar_init(uint32_t bar, int cnt) {
  asm volatile("mbarrier.init.shared::cta.b64 [%0], %1;" :: "r"(bar), "r"(cnt));
}
__device__ __forceinline__ void mbar_arrive(uint32_t bar, uint32_t cnt = 1) {
  asm volatile("mbarrier.arrive.shared::cta.b64 _, [%0], %1;" :: "r"(bar), "r"(cnt) : "memory");
}
__device__ __forceinline__ void mbar_wait(uint32_t bar, uint32_t parity) {
  asm volatile("{\n.reg .pred p;\n.reg .u32 c;\nmov.u32 c, 0;\n"
    "LAB_WAIT:\n"
    "mbarrier.try_wait.parity.shared::cta.b64 p, [%0], %1;\n"
    "@p bra DONE;\n"
    "add.u32 c, c, 1;\n"
    "setp.lt.u32 p, c, 400000;\n"
    "@p bra LAB_WAIT;\n"
    "DONE:\n}\n" :: "r"(bar), "r"(parity) : "memory");
}
#define ELECT_BEGIN "{\n.reg .pred p;\nelect.sync _|p, 0xffffffff;\n"
__device__ __forceinline__ void tma2d(uint32_t dst, const CUtensorMap* map, int c0, int c1, uint32_t bar, uint32_t bytes) {
  asm volatile(ELECT_BEGIN "@p mbarrier.arrive.expect_tx.shared::cta.b64 _, [%2], %5;\n"
    "@p cp.async.bulk.tensor.2d.shared::cluster.global.mbarrier::complete_tx::bytes [%0], [%1, {%3, %4}], [%2];\n}\n"
    :: "r"(dst), "l"(map), "r"(bar), "r"(c0), "r"(c1), "r"(bytes) : "memory");
}
__device__ __forceinline__ void tma2d_mc(uint32_t dst, const CUtensorMap* map, int c0, int c1, uint32_t bar) {
  asm volatile(ELECT_BEGIN
    "@p cp.async.bulk.tensor.2d.shared::cluster.global.mbarrier::complete_tx::bytes.multicast::cluster [%0], [%1, {%3, %4}], [%2], %5;\n}\n"
    :: "r"(dst), "l"(map), "r"(bar), "r"(c0), "r"(c1), "h"((uint16_t)3) : "memory");
}
__device__ __forceinline__ void tma2d_mc(uint32_t dst, const CUtensorMap* map, int c0, int c1, uint32_t bar, uint64_t pol) {
  asm volatile(ELECT_BEGIN
    "@p cp.async.bulk.tensor.2d.shared::cluster.global.mbarrier::complete_tx::bytes.multicast::cluster.L2::cache_hint [%0], [%1, {%3, %4}], [%2], %5, %6;\n}\n"
    :: "r"(dst), "l"(map), "r"(bar), "r"(c0), "r"(c1), "h"((uint16_t)3), "l"(pol) : "memory");
}
__device__ __forceinline__ void tma3d_hint(uint32_t dst, const CUtensorMap* map, int c1, uint32_t bar, uint64_t pol, uint32_t bytes) {
  asm volatile(ELECT_BEGIN "@p mbarrier.arrive.expect_tx.shared::cta.b64 _, [%2], %6;\n"
    "@p cp.async.bulk.tensor.3d.shared::cluster.global.mbarrier::complete_tx::bytes.L2::cache_hint [%0], [%1, {%3, %4, %3}], [%2], %5;\n}\n"
    :: "r"(dst), "l"(map), "r"(bar), "r"(0), "r"(c1), "l"(pol), "r"(bytes) : "memory");
}
__device__ __forceinline__ void bulk_load_pair(uint32_t dst, const void* src, uint32_t bar) {
  asm volatile(ELECT_BEGIN "@p mbarrier.arrive.expect_tx.shared::cta.b64 _, [%2], %3;\n"
    "@p cp.async.bulk.shared::cluster.global.mbarrier::complete_tx::bytes [%0], [%1], %3, [%2];\n}\n"
    :: "r"(dst), "l"(src), "r"(bar), "r"(PAIR) : "memory");
}
__device__ __forceinline__ void tma2d_store(const CUtensorMap* map, int c0, int c1, uint32_t src) {
  asm volatile("cp.async.bulk.tensor.2d.global.shared::cta.bulk_group [%0, {%1, %2}], [%3];"
    :: "l"(map), "r"(c0), "r"(c1), "r"(src) : "memory");
}
__device__ __forceinline__ uint64_t evict_first_policy() {
  uint64_t pol; asm volatile("createpolicy.fractional.L2::evict_first.b64 %0, 1.0;" : "=l"(pol)); return pol;
}
__device__ __forceinline__ void sched_sep(uint32_t zero) {
  asm volatile("{\n.reg .pred p;\n.reg .u32 c;\nSEP_L:\n.pragma \"nounroll\";\nmov.u32 c, %%clock;\nsetp.lt.u32 p, c, %0;\n@p bra SEP_L;\n}\n" :: "r"(zero) : "memory");
}
__device__ __forceinline__ void wg_fence() { asm volatile("wgmma.fence.sync.aligned;" ::: "memory"); }
__device__ __forceinline__ void wg_commit() { asm volatile("wgmma.commit_group.sync.aligned;" ::: "memory"); }
template<int N> __device__ __forceinline__ void wg_wait() { asm volatile("wgmma.wait_group.sync.aligned %0;" :: "n"(N) : "memory"); }
__device__ __forceinline__ void fence_regs(float (&d)[72]) {
  #pragma unroll
  for (int i = 0; i < 72; i++) asm volatile("" : "+f"(d[i]) :: "memory");
}
__device__ __forceinline__ void fence_async_smem() { asm volatile("fence.proxy.async.shared::cta;" ::: "memory"); }
template<int ID, int N> __device__ __forceinline__ void bar_sync() { asm volatile("bar.sync %0, %1;" :: "n"(ID), "n"(N) : "memory"); }
template<int ID, int N> __device__ __forceinline__ void bar_arrive() { asm volatile("bar.arrive %0, %1;" :: "n"(ID), "n"(N) : "memory"); }
__device__ __forceinline__ void cluster_sync() {
  asm volatile("barrier.cluster.arrive.relaxed.aligned;\nbarrier.cluster.wait.aligned;" ::: "memory");
}
__device__ __forceinline__ uint32_t pack_bf16(float lo, float hi) {
  uint32_t r; asm("cvt.rn.bf16x2.f32 %0, %1, %2;" : "=r"(r) : "f"(hi), "f"(lo)); return r;
}
__device__ __forceinline__ uint32_t max_bf16x2(uint32_t a, uint32_t b) {
  uint32_t r; asm("max.bf16x2 %0, %1, %2;" : "=r"(r) : "r"(a), "r"(b)); return r;
}
__device__ __forceinline__ uint32_t add_bf16x2(uint32_t a, uint32_t b) {
  uint32_t r; asm("add.rn.bf16x2 %0, %1, %2;" : "=r"(r) : "r"(a), "r"(b)); return r;
}
__device__ __forceinline__ uint32_t sub_bf16x2(uint32_t a, uint32_t b) {
  uint32_t r; asm("sub.rn.bf16x2 %0, %1, %2;" : "=r"(r) : "r"(a), "r"(b)); return r;
}
__device__ __forceinline__ uint32_t ex2_bf16x2(uint32_t a) {
  uint32_t r;
  asm("{\n.reg .b32 t;\nex2.approx.ftz.bf16x2 t, %1;\nmax.NaN.bf16x2 %0, t, %2;\n}\n" : "=r"(r) : "r"(a), "r"(0u));
  return r;
}
__device__ __forceinline__ void ex2_halves(uint32_t a, uint16_t& lo, uint16_t& hi) {
  asm volatile("{\n.reg .b16 l, h;\nmov.b32 {l, h}, %2;\nex2.approx.ftz.bf16 %0, l;\nex2.approx.ftz.bf16 %1, h;\n}\n" : "=h"(lo), "=h"(hi) : "r"(a));
}
__device__ __forceinline__ uint32_t pack_halves(uint16_t lo, uint16_t hi) {
  uint32_t r; asm volatile("mov.b32 %0, {%1, %2};" : "=r"(r) : "h"(lo), "h"(hi)); return r;
}
__device__ __forceinline__ uint32_t pack_halves_pin(uint16_t lo, uint16_t hi) {
  uint32_t r; asm volatile("{\n.reg .b32 t;\nmov.b32 t, {%1, %2};\nmax.NaN.bf16x2 %0, t, %3;\n}\n" : "=r"(r) : "h"(lo), "h"(hi), "r"(0u)); return r;
}
__device__ __forceinline__ float bf_lo(uint32_t v) { return __uint_as_float(v << 16); }
__device__ __forceinline__ float bf_hi(uint32_t v) { return __uint_as_float(v & 0xffff0000u); }
__device__ __forceinline__ void ldsm4t(uint32_t addr, uint32_t& a, uint32_t& b, uint32_t& c, uint32_t& d) {
  asm volatile("ldmatrix.sync.aligned.m8n8.x4.trans.shared.b16 {%0, %1, %2, %3}, [%4];"
    : "=r"(a), "=r"(b), "=r"(c), "=r"(d) : "r"(addr));
}
__device__ __forceinline__ void stsm4t(uint32_t addr, uint32_t a, uint32_t b, uint32_t c, uint32_t d) {
  asm volatile("stmatrix.sync.aligned.m8n8.x4.trans.shared.b16 [%0], {%1, %2, %3, %4};"
    :: "r"(addr), "r"(a), "r"(b), "r"(c), "r"(d));
}
__device__ __forceinline__ float4 lds128(uint32_t addr) {
  float4 v; asm volatile("ld.shared.v4.f32 {%0, %1, %2, %3}, [%4];" : "=f"(v.x), "=f"(v.y), "=f"(v.z), "=f"(v.w) : "r"(addr)); return v;
}
__device__ __forceinline__ void sts32(uint32_t addr, uint32_t v) { asm volatile("st.shared.u32 [%0], %1;" :: "r"(addr), "r"(v) : "memory"); }
__device__ __forceinline__ void red_max_f32(uint32_t addr, float v, bool on) {
  asm volatile("{\n.reg .pred p, q, e;\nsetp.ne.b32 e, %2, 0;\nsetp.ge.and.s32 p|q, %1, 0, e;\n"
               "@p red.shared.max.s32 [%0], %1;\n@q red.shared.min.u32 [%0], %1;\n}\n"
               :: "r"(addr), "r"(__float_as_uint(v)), "r"((uint32_t)on) : "memory");
}

#define ACC_REGS "{%0, %1, %2, %3, %4, %5, %6, %7, %8, %9, %10, %11, %12, %13, %14, %15, %16, %17, %18, %19, %20, %21, %22, %23, %24, %25, %26, %27, %28, %29, %30, %31, %32, %33, %34, %35, %36, %37, %38, %39, %40, %41, %42, %43, %44, %45, %46, %47, %48, %49, %50, %51, %52, %53, %54, %55, %56, %57, %58, %59, %60, %61, %62, %63, %64, %65, %66, %67, %68, %69, %70, %71}"
template<int TA, int OA, int OB>
__device__ __forceinline__ void mma(float (&d)[72], uint32_t a, uint32_t b) {
  asm volatile("{\n.reg .b64 da, db;\n.reg .b32 ta, tb, th;\n"
    "add.u32 ta, %72, %75;\nadd.u32 tb, %73, %76;\nmov.b32 th, 0x40000040;\n"
    "mov.b64 da, {ta, th};\nmov.b64 db, {tb, th};\n"
    "wgmma.mma_async.sync.aligned.m64n144k16.f32.bf16.bf16 " ACC_REGS ", da, db, 1, 1, 1, %74, 0;\n}\n"
    : "+f"(d[0]), "+f"(d[1]), "+f"(d[2]), "+f"(d[3]), "+f"(d[4]), "+f"(d[5]), "+f"(d[6]), "+f"(d[7]), "+f"(d[8]), "+f"(d[9]), "+f"(d[10]), "+f"(d[11]),
      "+f"(d[12]), "+f"(d[13]), "+f"(d[14]), "+f"(d[15]), "+f"(d[16]), "+f"(d[17]), "+f"(d[18]), "+f"(d[19]), "+f"(d[20]), "+f"(d[21]), "+f"(d[22]), "+f"(d[23]),
      "+f"(d[24]), "+f"(d[25]), "+f"(d[26]), "+f"(d[27]), "+f"(d[28]), "+f"(d[29]), "+f"(d[30]), "+f"(d[31]), "+f"(d[32]), "+f"(d[33]), "+f"(d[34]), "+f"(d[35]),
      "+f"(d[36]), "+f"(d[37]), "+f"(d[38]), "+f"(d[39]), "+f"(d[40]), "+f"(d[41]), "+f"(d[42]), "+f"(d[43]), "+f"(d[44]), "+f"(d[45]), "+f"(d[46]), "+f"(d[47]),
      "+f"(d[48]), "+f"(d[49]), "+f"(d[50]), "+f"(d[51]), "+f"(d[52]), "+f"(d[53]), "+f"(d[54]), "+f"(d[55]), "+f"(d[56]), "+f"(d[57]), "+f"(d[58]), "+f"(d[59]),
      "+f"(d[60]), "+f"(d[61]), "+f"(d[62]), "+f"(d[63]), "+f"(d[64]), "+f"(d[65]), "+f"(d[66]), "+f"(d[67]), "+f"(d[68]), "+f"(d[69]), "+f"(d[70]), "+f"(d[71])
    : "r"(a), "r"(b), "n"(TA), "n"(OA / 16), "n"(OB / 16));
}
template<int TA, int OA, int OB>
__device__ __forceinline__ void mma_init(float (&d)[72], uint32_t a, uint32_t b) {
  asm volatile("{\n.reg .b64 da, db;\n.reg .b32 ta, tb, th;\n"
    "add.u32 ta, %72, %75;\nadd.u32 tb, %73, %76;\nmov.b32 th, 0x40000040;\n"
    "mov.b64 da, {ta, th};\nmov.b64 db, {tb, th};\n"
    "wgmma.mma_async.sync.aligned.m64n144k16.f32.bf16.bf16 " ACC_REGS ", da, db, 0, 1, 1, %74, 0;\n}\n"
    : "=f"(d[0]), "=f"(d[1]), "=f"(d[2]), "=f"(d[3]), "=f"(d[4]), "=f"(d[5]), "=f"(d[6]), "=f"(d[7]), "=f"(d[8]), "=f"(d[9]), "=f"(d[10]), "=f"(d[11]),
      "=f"(d[12]), "=f"(d[13]), "=f"(d[14]), "=f"(d[15]), "=f"(d[16]), "=f"(d[17]), "=f"(d[18]), "=f"(d[19]), "=f"(d[20]), "=f"(d[21]), "=f"(d[22]), "=f"(d[23]),
      "=f"(d[24]), "=f"(d[25]), "=f"(d[26]), "=f"(d[27]), "=f"(d[28]), "=f"(d[29]), "=f"(d[30]), "=f"(d[31]), "=f"(d[32]), "=f"(d[33]), "=f"(d[34]), "=f"(d[35]),
      "=f"(d[36]), "=f"(d[37]), "=f"(d[38]), "=f"(d[39]), "=f"(d[40]), "=f"(d[41]), "=f"(d[42]), "=f"(d[43]), "=f"(d[44]), "=f"(d[45]), "=f"(d[46]), "=f"(d[47]),
      "=f"(d[48]), "=f"(d[49]), "=f"(d[50]), "=f"(d[51]), "=f"(d[52]), "=f"(d[53]), "=f"(d[54]), "=f"(d[55]), "=f"(d[56]), "=f"(d[57]), "=f"(d[58]), "=f"(d[59]),
      "=f"(d[60]), "=f"(d[61]), "=f"(d[62]), "=f"(d[63]), "=f"(d[64]), "=f"(d[65]), "=f"(d[66]), "=f"(d[67]), "=f"(d[68]), "=f"(d[69]), "=f"(d[70]), "=f"(d[71])
    : "r"(a), "r"(b), "n"(TA), "n"(OA / 16), "n"(OB / 16));
}
template<int OB>
__device__ __forceinline__ void mma_rs(float (&d)[72], uint32_t diag, uint32_t b) {
  asm volatile("{\n.reg .b64 db;\n.reg .b32 tb, th, z;\n"
    "add.u32 tb, %73, %74;\nmov.b32 th, 0x40000040;\nmov.b32 z, 0;\nmov.b64 db, {tb, th};\n"
    "wgmma.mma_async.sync.aligned.m64n144k16.f32.bf16.bf16 " ACC_REGS ", {%72, z, z, %72}, db, 1, 1, 1, 0;\n}\n"
    : "+f"(d[0]), "+f"(d[1]), "+f"(d[2]), "+f"(d[3]), "+f"(d[4]), "+f"(d[5]), "+f"(d[6]), "+f"(d[7]), "+f"(d[8]), "+f"(d[9]), "+f"(d[10]), "+f"(d[11]),
      "+f"(d[12]), "+f"(d[13]), "+f"(d[14]), "+f"(d[15]), "+f"(d[16]), "+f"(d[17]), "+f"(d[18]), "+f"(d[19]), "+f"(d[20]), "+f"(d[21]), "+f"(d[22]), "+f"(d[23]),
      "+f"(d[24]), "+f"(d[25]), "+f"(d[26]), "+f"(d[27]), "+f"(d[28]), "+f"(d[29]), "+f"(d[30]), "+f"(d[31]), "+f"(d[32]), "+f"(d[33]), "+f"(d[34]), "+f"(d[35]),
      "+f"(d[36]), "+f"(d[37]), "+f"(d[38]), "+f"(d[39]), "+f"(d[40]), "+f"(d[41]), "+f"(d[42]), "+f"(d[43]), "+f"(d[44]), "+f"(d[45]), "+f"(d[46]), "+f"(d[47]),
      "+f"(d[48]), "+f"(d[49]), "+f"(d[50]), "+f"(d[51]), "+f"(d[52]), "+f"(d[53]), "+f"(d[54]), "+f"(d[55]), "+f"(d[56]), "+f"(d[57]), "+f"(d[58]), "+f"(d[59]),
      "+f"(d[60]), "+f"(d[61]), "+f"(d[62]), "+f"(d[63]), "+f"(d[64]), "+f"(d[65]), "+f"(d[66]), "+f"(d[67]), "+f"(d[68]), "+f"(d[69]), "+f"(d[70]), "+f"(d[71])
    : "r"(diag), "r"(b), "n"(OB / 16));
}

__device__ __forceinline__ void store_acc_T(const float (&d)[72], uint32_t addr) {
  #pragma unroll
  for (int j = 0; j < 18; j += 2)
    stsm4t(addr + j * 1024, pack_bf16(d[4*j], d[4*j+1]), pack_bf16(d[4*j+2], d[4*j+3]),
           pack_bf16(d[4*j+4], d[4*j+5]), pack_bf16(d[4*j+6], d[4*j+7]));
}

template<bool IS_MAX>
__device__ __forceinline__ void warp_col_reduce(const uint32_t (&v)[18], uint32_t (&r3)[3], int lane) {
  #define OP(a, b) (IS_MAX ? max_bf16x2(a, b) : add_bf16x2(a, b))
  const bool b4 = lane & 16, b3 = lane & 8, b2 = lane & 4;
  uint32_t r1[9], r2[5];
  #pragma unroll
  for (int k = 0; k < 9; k++) {
    const uint32_t snd = b4 ? v[k] : v[k+9], kp = b4 ? v[k+9] : v[k];
    r1[k] = OP(kp, __shfl_xor_sync(0xffffffff, snd, 16));
  }
  #pragma unroll
  for (int k = 0; k < 4; k++) {
    const uint32_t snd = b3 ? r1[k] : r1[k+4], kp = b3 ? r1[k+4] : r1[k];
    r2[k] = OP(kp, __shfl_xor_sync(0xffffffff, snd, 8));
  }
  r2[4] = OP(r1[8], __shfl_xor_sync(0xffffffff, r1[8], 8));
  #pragma unroll
  for (int k = 0; k < 2; k++) {
    const uint32_t snd = b2 ? r2[k] : r2[k+2], kp = b2 ? r2[k+2] : r2[k];
    r3[k] = OP(kp, __shfl_xor_sync(0xffffffff, snd, 4));
  }
  r3[2] = OP(r2[4], __shfl_xor_sync(0xffffffff, r2[4], 4));
  #undef OP
}

constexpr uint32_t XLAP = 0x12435u, GLAP0 = 0x53241u, GLAP = 0x54321u;
struct Seg { int isq, head_or_k0, n, np; uint32_t lap, lap2; int lap0; };
__device__ __forceinline__ Seg seg_info(int n, int sh) {
  Seg s;
  s.isq = n <= 4 - sh;
  s.head_or_k0 = n == 0 ? 3 : (s.isq ? n - 1 : (n - 5 + sh) * 16);
  s.np = n == 6 ? 1 + sh : 0;
  s.n = n == 6 ? 49 - 15 * sh : 16;
  const bool g = n >= 2 && n <= 5;
  s.lap = g ? GLAP0 : XLAP;
  s.lap2 = g ? GLAP : XLAP;
  s.lap0 = n == 0 ? 4 : 0;
  return s;
}

__global__ void __launch_bounds__(384, 1) fused_kernel(const __grid_constant__ Params P) {
  extern __shared__ __align__(1024) char smem_raw[];
  const uint32_t sb = (smem_u32(smem_raw) + 1023u) & ~1023u;
  const uint32_t full0 = sb + OFF_BAR;
  const uint32_t emptyB = full0 + 48;
  const uint32_t emptyA = full0 + 192;
  const uint32_t stg0 = full0 + 96, maxbar = full0 + 104, stgfree = full0 + 112, ordy = full0 + 144;
  const uint32_t kvcnt = full0 + 128;
  const int tid = threadIdx.x;
  const int wg = __shfl_sync(0xffffffff, tid >> 7, 0);
  uint32_t rank; asm volatile("mov.u32 %0, %%cluster_ctarank;" : "=r"(rank));
  int cl;
  {
    const int c = blockIdx.x >> 1, t = c - 4;
    int set, idx;
    if (c < 4) { set = 1; idx = c; }
    else if (t < 32) { set = 2 * (t & 7); idx = t >> 3; }
    else { set = 2 * (1 + (t - 32) % 7) + 1; idx = (t - 32) / 7; }
    cl = set * 4 + idx;
    cl = (cl & 7) | (((cl >> 3) & 1) << 5) | ((cl >> 4) << 3);
  }
  const int blk = cl >> 5, b = ((cl >> 3) & 3) * 2 + rank, sub = cl & 7, sh = blk;
  uint4* const park = g_park + (cl * 2 + rank) * (2 * (PAIR / 16));

  if (tid == 0) {
    for (int i = 0; i < 6; i++) { mbar_init(full0 + 8*i, 1); mbar_init(emptyB + 8*i, 4); mbar_init(emptyA + 8*i, 2); }
    mbar_init(stg0, 8); mbar_init(maxbar, 8); mbar_init(stgfree, 1);
    for (int i = 0; i < 4; i++) mbar_init(ordy + 8*i, 1);
    asm volatile("fence.mbarrier_init.release.cluster;" ::: "memory");
  }
  if (tid < 288) sts32(sb + OFF_MAX + tid * 4, 0xff800000u);
  if (tid == 300) sts32(kvcnt, 0u);
  __syncthreads();
  cluster_sync();

  if (wg == 2) {
    asm volatile("setmaxnreg.dec.sync.aligned.u32 24;");
    const int warp = __shfl_sync(0xffffffff, (tid >> 5) & 3, 0);
    const int lane = tid & 31;
    const uint32_t ebar = warp == 0 ? emptyA : emptyB;
    #define ACQ(s) do { mbar_wait(ebar + 8*(s), (eph >> (s)) & 1); eph ^= 1u << (s); } while (0)
    if (warp == 0) {
      uint32_t eph = 0x3Fu;
      const uint64_t pol = evict_first_policy();
      int nkv = 0;
      #pragma unroll 1
      for (int n = 1 - sh; n < 7; n++) {
        Seg sg = seg_info(n, sh);
        const CUtensorMap* map = sg.isq ? &P.x[blk] : &P.os;
        const int row = (sg.isq ? 0 : blk * TOK) + b * SQ, k0 = sg.isq ? 0 : sg.head_or_k0;
        int lp = sg.lap0;
        #pragma unroll 1
        for (int j = 0; j < sg.n; j++) {
          const int s = (sg.lap >> (lp * 4)) & 15;
          const int kk = k0 + j - sg.np;
          if (j < sg.np) {
            if (j == 1) { mbar_wait(ordy + 16, 0); ACQ(s); bulk_load_pair(sb + s * PAIR, park, full0 + 8*s); }
          } else {
            if (!sg.isq && (kk & 15) == 0) mbar_wait(ordy + 8 * (kk >> 4), 0);
            ACQ(s);
            tma2d(sb + s * PAIR, map, kk * 64, row, full0 + 8*s, 18432 + 16384);
          }
          if (++lp == 5) { lp = 0; sg.lap = sg.lap2; }
        }
        #pragma unroll 1
        for (int q = (n >= 2 && n <= 5 ? 0 : 4); q < (n >= 1 && n <= 4 ? 8 : 4); q++) {
          if (sh && n == 4 && q == 4) { ACQ(5); bulk_load_pair(sb + 5 * PAIR, park + PAIR / 16, full0 + 40); }
          const int s = (0x32432432u >> (q * 4)) & 15;
          const int head = (q < 4 ? n - 2 : n - 1) * 8 + sub;
          ACQ(s);
          tma3d_hint(sb + s * PAIR, q < 4 ? &P.v[blk] : &P.k[blk], (b * 32 + head) * 512 + ((q < 4 ? q : q + 1) & 3) * 128, full0 + 8*s, pol, 32768);
          nkv++;
          asm volatile("st.volatile.shared.u32 [%0], %1;" :: "r"(kvcnt), "r"(nkv) : "memory");
        }
      }
    } else if (warp == 1) {
      const uint64_t pol = evict_first_policy();
      uint32_t eph = 0x3Fu;
      #pragma unroll 1
      for (int n = 1 - sh; n < 7; n++) {
        Seg sg = seg_info(n, sh);
        const int col = (sg.isq ? sg.head_or_k0 * 8 + sub : sub) * 128 + rank * 64, k0 = sg.isq ? 0 : sg.head_or_k0;
        int lp = sg.lap0;
        #pragma unroll 1
        for (int j = 0; j < sg.n; j++) {
          const int s = (sg.lap >> (lp * 4)) & 15;
          if (j >= sg.np) {
            ACQ(s);
            if (sg.isq) tma2d_mc(sb + s * PAIR + SLOT + rank * 8192, &P.wq[blk], col, j * 64, full0 + 8*s, pol);
            else tma2d_mc(sb + s * PAIR + SLOT + rank * 8192, &P.wo[blk], col, (k0 + j - sg.np) * 64, full0 + 8*s);
          }
          if (++lp == 5) { lp = 0; sg.lap = sg.lap2; }
        }
      }
    } else if (warp == 2) {
      uint32_t ph = 0;
      #define PARK_STORE(slot, pair) do { if (lane == 0) { mbar_wait(stg0, ph); \
          _Pragma("unroll 1") for (int pc = 0; pc < 12; pc++) \
            asm volatile("cp.async.bulk.global.shared::cta.bulk_group [%0], [%1], %2;" :: "l"(park + (slot) * (PAIR / 16) + pc * 192), "r"(sb + (pair) * PAIR + pc * 3072), "r"(3072) : "memory"); \
          asm volatile("cp.async.bulk.commit_group;" ::: "memory"); \
          asm volatile("cp.async.bulk.wait_group.read 0;" ::: "memory"); \
          if (pair) mbar_arrive(emptyA + 40, 2); else mbar_arrive(stgfree); } \
          ph ^= 1; __syncwarp(); } while (0)
      if (sh) PARK_STORE(1, 0);
      #pragma unroll 1
      for (int n = 0; n < 4; n++) {
        if (n == 2 && sh) PARK_STORE(0, 5);
        bar_sync<4, 288>();
        #pragma unroll
        for (int r = 0; r < 3; r++) {
          const int idx = r * 32 + lane;
          if (idx < 72) {
            float s0 = 0.f, s1 = 0.f;
            #pragma unroll
            for (int ww = 0; ww < 8; ww++) {
              uint32_t v; asm volatile("ld.shared.u32 %0, [%1];" : "=r"(v) : "r"(sb + OFF_SUM + ww * 288 + idx * 4));
              s0 += bf_lo(v); s1 += bf_hi(v);
            }
            asm volatile("st.shared.v2.f32 [%0], {%1, %2};" :: "r"(sb + OFF_INV + idx * 8), "f"(__fdividef(1.f, s0)), "f"(__fdividef(1.f, s1)) : "memory");
          }
        }
        bar_arrive<7, 160>();
        bar_arrive<8, 160>();
        if (lane == 0) {
          mbar_wait(stg0, ph);
          #pragma unroll 1
          for (int pc = 0; pc < 12; pc++)
            tma2d_store(&P.oss, (n * 8 + sub) * 128 + (pc & 1) * 64, blk * TOK + b * SQ + (pc >> 1) * 24, sb + (pc & 1) * SLOT + (pc >> 1) * 3072);
          asm volatile("cp.async.bulk.commit_group;" ::: "memory");
          asm volatile("cp.async.bulk.wait_group.read 0;" ::: "memory");
          mbar_arrive(stgfree);
          asm volatile("cp.async.bulk.wait_group 0;" ::: "memory");
          asm volatile("fence.proxy.async.global;" ::: "memory");
          asm volatile("red.release.gpu.global.add.u32 [%0], %1;" :: "l"(&g_cnt[(blk * 8 + b) * 4 + n]), "r"(1u) : "memory");
        }
        ph ^= 1;
        __syncwarp();
      }
      if (lane == 0) {
        mbar_wait(stg0, ph);
        tma2d_store(&P.out, blk * 1024 + sub * 128, b * SQ, sb);
        tma2d_store(&P.out, blk * 1024 + sub * 128 + 64, b * SQ, sb + SLOT);
        asm volatile("cp.async.bulk.commit_group;" ::: "memory");
        asm volatile("cp.async.bulk.wait_group.read 0;" ::: "memory");
      }
    } else {
      unsigned int epoch;
      asm volatile("ld.relaxed.gpu.global.u32 %0, [%1];" : "=r"(epoch) : "l"(&g_done) : "memory");
      const unsigned int target = 8u * ((epoch >> 7) + 1);
      {
        const char* kp = P.kptr[blk] + (size_t)(b * 32 + sub) * (512 * 256) + lane * 256;
        uint32_t v0 = 0, v1 = 0;
        uint32_t tnext = (uint32_t)clock64() + 2000;
        int q = 0;
        #pragma unroll 1
        for (int spin = 0; spin < 1000000 && q < 8; spin++) {
          int cnt; asm volatile("ld.volatile.shared.u32 %0, [%1];" : "=r"(cnt) : "r"(kvcnt) : "memory");
          if (q < cnt * 2) q = cnt * 2;
          const uint32_t now = (uint32_t)clock64();
          if ((int)(now - tnext) >= 0 && q < 8) {
            const char* a = kp + ((q + 2) & 7) * 16384;
            asm volatile("st.volatile.shared.u32 [%0], %1;" :: "r"(kvcnt + 8), "r"(v0 ^ v1) : "memory");
            asm volatile("ld.global.L2::256B.u32 %0, [%1];" : "=r"(v0) : "l"(a) : "memory");
            asm volatile("ld.global.L2::256B.u32 %0, [%1];" : "=r"(v1) : "l"(a + 8192) : "memory");
            q++; tnext = now + 1400;
          } else __nanosleep(50);
        }
        asm volatile("st.volatile.shared.u32 [%0], %1;" :: "r"(kvcnt + 8), "r"(v0 ^ v1) : "memory");
      }
      int nrdy = 0;
      #pragma unroll 1
      for (int spin = 0; spin < 1000000 && nrdy < 4; spin++) {
        int cnt; asm volatile("ld.volatile.shared.u32 %0, [%1];" : "=r"(cnt) : "r"(kvcnt) : "memory");
        if (cnt >= nrdy * 8 + 8) {
          unsigned int c; asm volatile("ld.acquire.gpu.global.u32 %0, [%1];" : "=r"(c) : "l"(&g_cnt[(blk * 8 + b) * 4 + nrdy]) : "memory");
          if ((int)(c - target) >= 0) {
            asm volatile("fence.proxy.async.global;" ::: "memory");
            __syncwarp();
            if (lane == 0) mbar_arrive(ordy + 8 * nrdy);
            nrdy++;
          }
        }
        __nanosleep(100);
      }
      if (lane == 0) atomicAdd(&g_done, 1u);
    }
    __syncwarp();
    cluster_sync();
  } else {
    asm volatile("setmaxnreg.inc.sync.aligned.u32 240;");
    const int w = wg;
    int t128 = tid & 127;
    asm volatile("" : "+r"(t128));
    #define lane (t128 & 31)
    #define warp (t128 >> 5)
    const uint32_t st_base = sb + w * SLOT + (uint32_t)(((lane >> 4) * 8 + (lane & 7)) * 128 + (((2 * warp + ((lane >> 3) & 1)) ^ (lane & 7)) << 4));
    const uint32_t d0 = ((sb & 0x3FFFF) >> 4) | (64u << 16);
    const uint32_t d0w = d0 + w * 512, d0v = d0 + w * 1024;
    uint32_t rel_addr; asm("mapa.shared::cluster.u32 %0, %1, %2;" : "=r"(rel_addr) : "r"(t128 == 0 ? emptyA : emptyB), "r"(t128 == 0 ? rank : (uint32_t)(t128 & 1)));
    #define WAITF(s, flip) mbar_wait(full0 + 8*(s), ((fph >> (s)) & 1) ^ (flip))
    #define RELX(s, all) asm volatile("{\n.reg .pred p;\nsetp.lt.u32 p, %1, %2;\n@p mbarrier.arrive.relaxed.cluster.shared::cluster.b64 _, [%0];\n}\n" :: "r"(rel_addr + 8*(s)), "r"(t128), "r"((all) ? 3 : 1) : "memory")
    #define REL(s) RELX(s, true)
    #define STG_ARRIVE() do { fence_async_smem(); __syncwarp(); if (lane == 0) mbar_arrive(stg0); } while (0)
    #define STG_FREE() do { mbar_wait(stgfree, sfp); sfp ^= 1; } while (0)
    #define TURN_WAIT() do { if (w) bar_sync<6, 256>(); else bar_sync<5, 256>(); } while (0)
    #define TURN_PASS() do { if (w) bar_arrive<5, 256>(); else bar_arrive<6, 256>(); } while (0)
    #define GMMA(acc, da, db, O, first) do { if (!(first)) fence_regs(acc); wg_fence(); \
        if (first) mma_init<1, (O) + SLOT, (O)>(acc, da, db); else mma<1, (O) + SLOT, (O)>(acc, da, db); \
        mma<1, (O) + SLOT + 2048, (O) + 32>(acc, da, db); mma<1, (O) + SLOT + 4096, (O) + 64>(acc, da, db); \
        mma<1, (O) + SLOT + 6144, (O) + 96>(acc, da, db); wg_commit(); } while (0)
    #define O_STSM() do { _Pragma("unroll") for (int c_ = 0; c_ < 9; c_++) \
        stsm4t(st_base + c_ * 2048, ok[4*c_], ok[4*c_+1], ok[4*c_+2], ok[4*c_+3]); } while (0)
    const float cs = 0.08838834764831845f * 1.4426950408889634f;
    uint32_t fph = 0, sfp = 0;
    uint32_t ok[36];
    #pragma unroll
    for (int i = 0; i < 36; i++) ok[i] = 0;
    #pragma unroll 1
    for (int h = -sh; h < 5; h++) {
      if (h <= 0 || h == 4) {
        const Seg sg = seg_info(h <= 0 ? h + 1 : 6, sh);
        float a0[72];
        #pragma unroll
        for (int i = 0; i < 72; i++) a0[i] = 0.f;
        int lp = sg.lap0, sprev = 0;
        if (h == 4) {
          if (!w) bar_sync<5, 256>();
          const uint32_t dg = (lane >> 3) == (lane & 3) ? ((lane & 4) ? 0x3f800000u : 0x00003f80u) : 0u;
          const uint32_t db = d0 + w * (SLOT / 16);
          const uint32_t g0 = warp == 0 ? dg : 0u, g1 = warp == 1 ? dg : 0u, g2 = warp == 2 ? dg : 0u, g3 = warp == 3 ? dg : 0u;
          #define FOLD(p) do { fence_regs(a0); wg_fence(); \
              mma_rs<(p) * PAIR>(a0, g0, db); mma_rs<(p) * PAIR + 32>(a0, g1, db); mma_rs<(p) * PAIR + 64>(a0, g2, db); mma_rs<(p) * PAIR + 96>(a0, g3, db); \
              wg_commit(); } while (0)
          O_STSM(); FOLD(5); STG_ARRIVE(); wg_wait<0>(); fence_regs(a0); REL(5);
          if (sh) { WAITF(3, 0); FOLD(3); wg_wait<0>(); fence_regs(a0); REL(3); fph ^= 0x08u; }
          lp = sg.np;
        }
        #pragma unroll 1
        for (int j = sg.np; j < sg.n; j++) {
          const int s = (XLAP >> (lp * 4)) & 15;
          WAITF(s, 0); fph ^= 1u << s;
          const uint32_t off = s * (PAIR / 16);
          GMMA(a0, d0w + off, d0 + off, 0, false);
          wg_wait<1>();
          if (j > sg.np) RELX(sprev, !(h >= 0 && j > sg.n - 5 && sprev >= 2 && sprev <= 4));
          sprev = s;
          if (++lp == 5) lp = 0;
        }
        if (h == 4) STG_FREE();
        wg_wait<0>();
        fence_regs(a0);
        if (h == 0) bar_sync<3, 256>(); else REL(sprev);
        const float f = h == 4 ? 1.f : cs;
        #pragma unroll
        for (int i = 0; i < 72; i++) a0[i] *= f;
        store_acc_T(a0, st_base + (h == 0 ? 5 * PAIR : 0));
        fence_async_smem();
        if (h != 0) { __syncwarp(); if (lane == 0) mbar_arrive(stg0); continue; }
        if (w) bar_arrive<5, 256>();
      }
      const uint32_t hodd = h & 1;
      const bool last = h == 3, gq = h + sh < 3;
      const uint32_t ma = sb + OFF_MAX + hodd * 576 + (lane & 3) * 144;
      uint32_t sp[3][36];
      uint32_t l2[18];
      uint32_t mx[18];
      {
        #define PACK(s, i) do { _Pragma("unroll") for (int j = 0; j < 18; j++) { \
            sp[i][2*j] = pack_bf16(s[4*j], s[4*j+1]); sp[i][2*j+1] = pack_bf16(s[4*j+2], s[4*j+3]); \
            const uint32_t m2 = max_bf16x2(sp[i][2*j], sp[i][2*j+1]); \
            mx[j] = (i) ? max_bf16x2(mx[j], m2) : m2; \
            asm volatile("" : "+r"(sp[i][2*j]), "+r"(sp[i][2*j+1]), "+r"(mx[j]) :: "memory"); } } while (0)
        #define SISSUE(s, p, fin) do { TURN_WAIT(); wg_fence(); \
            mma_init<0, (p) * PAIR, 5 * PAIR>(s, d0w, d0);      mma<0, (p) * PAIR + 32, 5 * PAIR + 32>(s, d0w, d0); \
            mma<0, (p) * PAIR + 64, 5 * PAIR + 64>(s, d0w, d0); mma<0, (p) * PAIR + 96, 5 * PAIR + 96>(s, d0w, d0); \
            mma<0, (p) * PAIR + 16384, 5 * PAIR + SLOT>(s, d0w, d0);           mma<0, (p) * PAIR + 16384 + 32, 5 * PAIR + SLOT + 32>(s, d0w, d0); \
            mma<0, (p) * PAIR + 16384 + 64, 5 * PAIR + SLOT + 64>(s, d0w, d0); mma<0, (p) * PAIR + 16384 + 96, 5 * PAIR + SLOT + 96>(s, d0w, d0); \
            wg_commit(); if (!(fin) || !w) TURN_PASS(); } while (0)
        float sa[72], sc[72], s[72];
        WAITF(3, 0);
        SISSUE(sa, 3, false);
        if (h > 0) O_STSM();
        wg_wait<0>(); fence_regs(sa); RELX(3, false);
        WAITF(4, 0);
        SISSUE(sc, 4, false);
        sched_sep(P.zero);
        PACK(sa, 0);
        if (h > 0) STG_ARRIVE();
        sched_sep(P.zero);
        wg_wait<0>(); fence_regs(sc); REL(4);
        PACK(sc, 1);
        WAITF(2, 0);
        SISSUE(sc, 2, false);
        wg_wait<0>(); fence_regs(sc); REL(2);
        PACK(sc, 2);
        WAITF(3, 1);
        SISSUE(s, 3, true);
        wg_wait<0>(); fence_regs(s); REL(3); REL(5);
        if (h + sh > 0) STG_FREE();
        #pragma unroll
        for (int c = 0; c < 9; c++) {
          const uint32_t k0 = pack_bf16(s[8*c], s[8*c+1]), k1 = pack_bf16(s[8*c+2], s[8*c+3]);
          const uint32_t k2 = pack_bf16(s[8*c+4], s[8*c+5]), k3 = pack_bf16(s[8*c+6], s[8*c+7]);
          stsm4t(st_base + c * 2048, k0, k1, k2, k3);
          mx[2*c] = max_bf16x2(mx[2*c], max_bf16x2(k0, k1));
          mx[2*c+1] = max_bf16x2(mx[2*c+1], max_bf16x2(k2, k3));
          asm volatile("" : "+r"(mx[2*c]), "+r"(mx[2*c+1]) :: "memory");
        }
      }
      fph ^= 0x14u;
      {
        float a0[72];
        #define U0(j) ((j) <= 2 ? 0 : ((j) >= 16 ? 27 : (((j) - 2) * 27) / 14))
        uint32_t mm[2][2], pk[2][4];
        float4 mr;
        uint16_t eh[2][8];
        #define GP(j) ((j) < 0 ? 1 : ((j) < 5 ? (int)((GLAP0 >> (((j) & 7) * 4)) & 15) : 1 + (j) % 5))
        #define GSTEP(j) do { \
          WAITF(GP(j), ((j) / 5) & 1); \
          if ((j) > 0) { wg_wait<0>(); if ((j) < 15) RELX(GP((j) - 1), (j) < 12); } \
          if ((j) == 1) mbar_wait(maxbar, hodd); \
          GMEM(j); \
          GMMA(a0, d0w, d0, GP(j) * PAIR, (j) == 0); \
          if ((j) == 0) { \
            uint32_t r3[3]; warp_col_reduce<true>(mx, r3, lane); \
            const int jb = (lane & 16) ? 9 : 0, j0 = jb + ((lane & 8) ? 4 : 0) + ((lane & 4) ? 2 : 0); \
            red_max_f32(ma + j0 * 8, bf_lo(r3[0]), true);      red_max_f32(ma + j0 * 8 + 4, bf_hi(r3[0]), true); \
            red_max_f32(ma + j0 * 8 + 8, bf_lo(r3[1]), true);  red_max_f32(ma + j0 * 8 + 12, bf_hi(r3[1]), true); \
            red_max_f32(ma + (jb + 8) * 8, bf_lo(r3[2]), !(lane & 12)); red_max_f32(ma + (jb + 8) * 8 + 4, bf_hi(r3[2]), !(lane & 12)); \
            __syncwarp(); if (lane == 0) mbar_arrive(maxbar); } \
          GEXP(j); } while (0)
        #define GMEM(j) do { \
          _Pragma("unroll") for (int u = U0(j); u < U0((j) + 1); u++) if (u % 3 == 0) { \
            mm[(u / 3) & 1][0] = __byte_perm(__float_as_uint(mr.x), __float_as_uint(mr.y), 0x7632); \
            mm[(u / 3) & 1][1] = __byte_perm(__float_as_uint(mr.z), __float_as_uint(mr.w), 0x7632); } \
          _Pragma("unroll") for (int u = U0((j) - 1); u < U0(j); u++) if (u % 3 == 0) { \
            const int c = u / 3; uint16_t (&e)[8] = eh[u - U0((j) - 1)]; \
            const uint32_t k0 = pack_halves(e[0], e[1]), k1 = pack_halves(e[2], e[3]), k2 = pack_halves(e[4], e[5]), k3 = pack_halves(e[6], e[7]); \
            stsm4t(st_base + c * 2048, k0, k1, k2, k3); \
            l2[2*c] = add_bf16x2(k0, k1); l2[2*c+1] = add_bf16x2(k2, k3); asm volatile("" : "+r"(l2[2*c]), "+r"(l2[2*c+1])); } \
          _Pragma("unroll") for (int u = U0((j) + 1); u < U0((j) + 2); u++) if (u % 3 == 0) { \
            const int c = u / 3; \
            mr = lds128(ma + c * 16); \
            ldsm4t(st_base + c * 2048, pk[c & 1][0], pk[c & 1][1], pk[c & 1][2], pk[c & 1][3]); \
          } } while (0)
        #define GEXP(j) do { \
          _Pragma("unroll") for (int u = U0((j) - 1); u < U0(j); u++) if (u % 3) { \
            const int c = u / 3, t = u % 3; uint16_t (&e)[8] = eh[u - U0((j) - 1)]; \
            uint32_t (&q)[36] = sp[t ? t - 1 : 0]; \
            q[4*c] = pack_halves_pin(e[0], e[1]); q[4*c+1] = pack_halves_pin(e[2], e[3]); \
            q[4*c+2] = pack_halves_pin(e[4], e[5]); q[4*c+3] = pack_halves_pin(e[6], e[7]); \
            l2[2*c] = add_bf16x2(l2[2*c], add_bf16x2(q[4*c], q[4*c+1])); l2[2*c+1] = add_bf16x2(l2[2*c+1], add_bf16x2(q[4*c+2], q[4*c+3])); \
            asm volatile("" : "+r"(l2[2*c]), "+r"(l2[2*c+1])); \
          } \
          _Pragma("unroll") for (int u = U0(j); u < U0((j) + 1); u++) { \
            const int c = u / 3, t = u % 3; uint16_t (&e)[8] = eh[u - U0(j)]; \
            const uint32_t* q = t ? &sp[t ? t - 1 : 0][4*c] : pk[c & 1]; \
            ex2_halves(sub_bf16x2(q[0], mm[c & 1][0]), e[0], e[1]); ex2_halves(sub_bf16x2(q[1], mm[c & 1][0]), e[2], e[3]); \
            ex2_halves(sub_bf16x2(q[2], mm[c & 1][1]), e[4], e[5]); ex2_halves(sub_bf16x2(q[3], mm[c & 1][1]), e[6], e[7]); \
            if (t == 1) { \
              sp[2][4*c] = sub_bf16x2(sp[2][4*c], mm[c & 1][0]); sp[2][4*c+1] = sub_bf16x2(sp[2][4*c+1], mm[c & 1][0]); \
              sp[2][4*c+2] = sub_bf16x2(sp[2][4*c+2], mm[c & 1][1]); sp[2][4*c+3] = sub_bf16x2(sp[2][4*c+3], mm[c & 1][1]); \
              asm volatile("" : "+r"(sp[2][4*c]), "+r"(sp[2][4*c+1]), "+r"(sp[2][4*c+2]), "+r"(sp[2][4*c+3])); } \
          } } while (0)
        GSTEP(0); GSTEP(1); GSTEP(2); GSTEP(3); GSTEP(4); GSTEP(5); GSTEP(6); GSTEP(7);
        GSTEP(8); GSTEP(9); GSTEP(10); GSTEP(11); GSTEP(12); GSTEP(13); GSTEP(14); GSTEP(15);
        fph ^= 0x3Cu;
        WAITF(2, 0);
        GMEM(16); GEXP(16);
        fence_async_smem();
        bar_sync<3, 256>();
        wg_wait<0>();
        fence_regs(a0);
        if (w) bar_arrive<10, 256>();
        if (gq) {
          #pragma unroll
          for (int i = 0; i < 72; i++) a0[i] *= cs;
        }
        store_acc_T(a0, st_base + 5 * PAIR);
        if (!gq && !last) STG_ARRIVE();
      }
      float o[72];
      #define STORE_P(i) do { _Pragma("unroll") for (int c_ = 0; c_ < 9; c_++) \
          stsm4t(st_base + ((i) & 1) * PAIR + c_ * 2048, sp[(i)-1][4*c_], sp[(i)-1][4*c_+1], sp[(i)-1][4*c_+2], sp[(i)-1][4*c_+3]); } while (0)
      #define PVSTEP(i) do { \
        constexpr int v_ = (i) == 3 ? 2 : 2 + (i), pb_ = ((i) & 1) * PAIR; \
        if ((i) > 0) { \
          if (!w) { bar_sync<9 + ((i) & 1), 256>(); STORE_P((i) ? (i) : 1); } \
          if ((i) == 3) { \
            uint32_t r3[3]; \
            warp_col_reduce<false>(l2, r3, lane); \
            const int jb = (lane & 16) ? 9 : 0, j0 = jb + ((lane & 8) ? 4 : 0) + ((lane & 4) ? 2 : 0); \
            const uint32_t sa = sb + OFF_SUM + (w * 4 + warp) * 288 + (lane & 3) * 72; \
            sts32(sa + j0 * 4, r3[0]); sts32(sa + j0 * 4 + 4, r3[1]); sts32(sa + (jb + 8) * 4, r3[2]); \
            if (t128 < 72) sts32(sb + OFF_MAX + (hodd ^ 1) * 576 + w * 288 + t128 * 4, 0xff800000u); \
            bar_arrive<4, 288>(); } \
          wg_wait<0>(); \
          RELX(1 + (i), (i) > 1 && last && !(sh && (i) == 2)); \
          if (w && (i) < 3) bar_arrive<10 - ((i) & 1), 256>(); \
          if (!w) fence_async_smem(); \
          WAITF(v_, (i) == 3); \
        } \
        if (!w) { if ((i) > 0) bar_sync<5, 256>(); } else { \
          bar_sync<6, 256>(); \
          if ((i) < 3) STORE_P((i) < 3 ? (i) + 1 : 1); \
        } \
        if ((i) > 0) fence_regs(o); \
        wg_fence(); \
        if ((i) == 0) mma_init<1, v_ * PAIR, pb_>(o, d0v, d0); else mma<1, v_ * PAIR, pb_>(o, d0v, d0); \
        mma<1, v_ * PAIR + 2048, pb_ + 32>(o, d0v, d0); mma<1, v_ * PAIR + 4096, pb_ + 64>(o, d0v, d0); mma<1, v_ * PAIR + 6144, pb_ + 96>(o, d0v, d0); \
        mma<1, v_ * PAIR + 8192, pb_ + SLOT>(o, d0v, d0);       mma<1, v_ * PAIR + 10240, pb_ + SLOT + 32>(o, d0v, d0); \
        mma<1, v_ * PAIR + 12288, pb_ + SLOT + 64>(o, d0v, d0); mma<1, v_ * PAIR + 14336, pb_ + SLOT + 96>(o, d0v, d0); \
        wg_commit(); \
        if (!w) bar_arrive<6, 256>(); \
        if ((i) < 3) { sched_sep(P.zero); \
            \
          if ((i) < 2) { _Pragma("unroll") for (int r_ = (i) * 18; r_ < (i) * 18 + 18; r_++) { sp[2][r_] = ex2_bf16x2(sp[2][r_]); asm volatile("" : "+r"(sp[2][r_])); } } \
          else { _Pragma("unroll") for (int r_ = 0; r_ < 18; r_++) \
              asm volatile("{\n.reg .b32 t;\nadd.rn.bf16x2 t, %1, %2;\nadd.rn.bf16x2 %0, %0, t;\n}\n" : "+r"(l2[r_]) : "r"(sp[2][2*r_]), "r"(sp[2][2*r_+1])); } \
          sched_sep(P.zero); } \
        if (w) { if ((i) < 3) fence_async_smem(); bar_arrive<5, 256>(); } } while (0)
      PVSTEP(0);
      PVSTEP(1);
      PVSTEP(2);
      PVSTEP(3);
      fph ^= 0x18u;
      wg_wait<0>();
      fence_regs(o);
      RELX(2, last); REL(1);
      if (w) bar_sync<8, 160>(); else bar_sync<7, 160>();
      #pragma unroll
      for (int j = 0; j < 9; j++) {
        const float4 iv = lds128(sb + OFF_INV + (lane & 3) * 144 + j * 16);
        ok[4*j]   = pack_bf16(o[8*j] * iv.x, o[8*j+1] * iv.y);   ok[4*j+1] = pack_bf16(o[8*j+2] * iv.x, o[8*j+3] * iv.y);
        ok[4*j+2] = pack_bf16(o[8*j+4] * iv.z, o[8*j+5] * iv.w); ok[4*j+3] = pack_bf16(o[8*j+6] * iv.z, o[8*j+7] * iv.w);
      }
      if (sh && h == 2) { WAITF(5, 0); fph ^= 0x20u; }
    }
    cluster_sync();
    #undef lane
    #undef warp
  }
}

typedef CUresult (*PFN_enc)(CUtensorMap*, CUtensorMapDataType, cuuint32_t, void*, const cuuint64_t*, const cuuint64_t*,
                            const cuuint32_t*, const cuuint32_t*, CUtensorMapInterleave, CUtensorMapSwizzle,
                            CUtensorMapL2promotion, CUtensorMapFloatOOBfill);

void enc2d(PFN_enc enc, CUtensorMap* m, const void* p, uint64_t cols, uint64_t rows, uint32_t box_rows) {
  cuuint64_t dims[2] = {cols, rows}; cuuint64_t st[1] = {cols * 2};
  cuuint32_t box[2] = {64, box_rows}; cuuint32_t es[2] = {1, 1};
  enc(m, CU_TENSOR_MAP_DATA_TYPE_BFLOAT16, 2, (void*)p, dims, st, box, es, CU_TENSOR_MAP_INTERLEAVE_NONE,
      CU_TENSOR_MAP_SWIZZLE_128B, CU_TENSOR_MAP_L2_PROMOTION_L2_128B, CU_TENSOR_MAP_FLOAT_OOB_FILL_NONE);
}
void enc3d(PFN_enc enc, CUtensorMap* m, const void* p, uint64_t rows) {
  cuuint64_t dims[3] = {64, rows, 2}; cuuint64_t st[2] = {256, 128};
  cuuint32_t box[3] = {64, 128, 2}; cuuint32_t es[3] = {1, 1, 1};
  enc(m, CU_TENSOR_MAP_DATA_TYPE_BFLOAT16, 3, (void*)p, dims, st, box, es, CU_TENSOR_MAP_INTERLEAVE_NONE,
      CU_TENSOR_MAP_SWIZZLE_128B, CU_TENSOR_MAP_L2_PROMOTION_L2_256B, CU_TENSOR_MAP_FLOAT_OOB_FILL_NONE);
}

}

extern "C" void kernel_launch(void* const* d_in, const int* in_sizes, int n_in, void* d_out, int out_size) {
  (void)in_sizes; (void)n_in; (void)out_size;
  void* fn = nullptr; cudaDriverEntryPointQueryResult q;
  cudaGetDriverEntryPoint("cuTensorMapEncodeTiled", &fn, cudaEnableDefault, &q);
  PFN_enc enc = (PFN_enc)fn;
  void* oscr = nullptr; cudaGetSymbolAddress(&oscr, g_oscr);
  Params P;
  for (int i = 0; i < 2; i++) {
    enc2d(enc, &P.x[i], d_in[5*i + 0], 1024, TOK, SQ);
    enc3d(enc, &P.k[i], d_in[5*i + 1], 8 * 32 * 512);
    enc3d(enc, &P.v[i], d_in[5*i + 2], 8 * 32 * 512);
    enc2d(enc, &P.wq[i], d_in[5*i + 3], 4096, 1024, 64);
    enc2d(enc, &P.wo[i], d_in[5*i + 4], 1024, 4096, 64);
    P.kptr[i] = (const char*)d_in[5*i + 1];
  }
  enc2d(enc, &P.os, oscr, 4096, 2 * TOK, SQ);
  enc2d(enc, &P.oss, oscr, 4096, 2 * TOK, 24);
  enc2d(enc, &P.out, d_out, 2048, TOK, SQ);
  P.zero = 0;
  cudaFuncSetAttribute(fused_kernel, cudaFuncAttributeMaxDynamicSharedMemorySize, SMEM_BYTES);
  cudaLaunchConfig_t cfg = {};
  cfg.gridDim = dim3(NCTA); cfg.blockDim = dim3(384); cfg.dynamicSmemBytes = SMEM_BYTES; cfg.stream = cudaStreamPerThread;
  cudaLaunchAttribute at[1];
  at[0].id = cudaLaunchAttributeClusterDimension; at[0].val.clusterDim.x = 2; at[0].val.clusterDim.y = 1; at[0].val.clusterDim.z = 1;
  cfg.attrs = at; cfg.numAttrs = 1;
  cudaLaunchKernelEx(&cfg, fused_kernel, P);
}
```

```cpp
#include <cuda_runtime.h>
#include <cuda.h>
#include <cuda_bf16.h>
#include <stdint.h>

namespace {

constexpr int SQ = 144;
constexpr int TOK = 1152;
constexpr int SLOT = 18432;
constexpr int PAIR = 2 * SLOT;
constexpr int OFF_BAR = 6 * PAIR;
constexpr int OFF_MAX = OFF_BAR + 256;
constexpr int OFF_SUM = OFF_MAX + 2 * 576;
constexpr int OFF_INV = OFF_SUM + 8 * 288;
constexpr int SMEM_BYTES = OFF_INV + 576 + 1024;
constexpr int NCTA = 128;

struct alignas(64) Params {
  CUtensorMap x[2], wq[2], k[2], v[2], wo[2], os, oss, out;
  const char* kptr[2];
  uint32_t zero;
};

__device__ __nv_bfloat16 g_oscr[2 * TOK * 4096];
__device__ uint4 g_park[NCTA * 2 * (PAIR / 16)];
__device__ unsigned int g_cnt[64];
__device__ unsigned int g_done;

__device__ __forceinline__ uint32_t smem_u32(const void* p) { return (uint32_t)__cvta_generic_to_shared(p); }
__device__ __forceinline__ void mbar_init(uint32_t bar, int cnt) {
  asm volatile("mbarrier.init.shared::cta.b64 [%0], %1;" :: "r"(bar), "r"(cnt));
}
__device__ __forceinline__ void mbar_arrive(uint32_t bar, uint32_t cnt = 1) {
  asm volatile("mbarrier.arrive.shared::cta.b64 _, [%0], %1;" :: "r"(bar), "r"(cnt) : "memory");
}
__device__ __forceinline__ void mbar_wait(uint32_t bar, uint32_t parity) {
  asm volatile("{\n.reg .pred p;\n.reg .u32 c;\nmov.u32 c, 0;\n"
    "LAB_WAIT:\n"
    "mbarrier.try_wait.parity.shared::cta.b64 p, [%0], %1;\n"
    "@p bra DONE;\n"
    "add.u32 c, c, 1;\n"
    "setp.lt.u32 p, c, 400000;\n"
    "@p bra LAB_WAIT;\n"
    "DONE:\n}\n" :: "r"(bar), "r"(parity) : "memory");
}
#define ELECT_BEGIN "{\n.reg .pred p;\nelect.sync _|p, 0xffffffff;\n"
__device__ __forceinline__ void tma2d_mc(uint32_t dst, const CUtensorMap* map, int c0, int c1, uint32_t bar) {
  asm volatile(ELECT_BEGIN
    "@p cp.async.bulk.tensor.2d.shared::cluster.global.mbarrier::complete_tx::bytes.multicast::cluster [%0], [%1, {%3, %4}], [%2], %5;\n}\n"
    :: "r"(dst), "l"(map), "r"(bar), "r"(c0), "r"(c1), "h"((uint16_t)3) : "memory");
}
__device__ __forceinline__ void tma3d(uint32_t dst, const CUtensorMap* map, int c1, int c2, uint32_t bar, uint32_t bytes, uint64_t pol) {
  asm volatile(ELECT_BEGIN "@p mbarrier.arrive.expect_tx.shared::cta.b64 _, [%2], %6;\n"
    "@p cp.async.bulk.tensor.3d.shared::cluster.global.mbarrier::complete_tx::bytes.L2::cache_hint [%0], [%1, {%3, %4, %5}], [%2], %7;\n}\n"
    :: "r"(dst), "l"(map), "r"(bar), "r"(0), "r"(c1), "r"(c2), "r"(bytes), "l"(pol) : "memory");
}
__device__ __forceinline__ void bulk_load_pair(uint32_t dst, const void* src, uint32_t bar) {
  asm volatile(ELECT_BEGIN "@p mbarrier.arrive.expect_tx.shared::cta.b64 _, [%2], %3;\n"
    "@p cp.async.bulk.shared::cluster.global.mbarrier::complete_tx::bytes [%0], [%1], %3, [%2];\n}\n"
    :: "r"(dst), "l"(src), "r"(bar), "r"(PAIR) : "memory");
}
__device__ __forceinline__ void tma2d_store(const CUtensorMap* map, int c0, int c1, uint32_t src) {
  asm volatile("cp.async.bulk.tensor.2d.global.shared::cta.bulk_group [%0, {%1, %2}], [%3];"
    :: "l"(map), "r"(c0), "r"(c1), "r"(src) : "memory");
}
__device__ __forceinline__ uint64_t evict_first_policy() {
  uint64_t pol; asm volatile("createpolicy.fractional.L2::evict_first.b64 %0, 1.0;" : "=l"(pol)); return pol;
}
__device__ __forceinline__ void sched_sep(uint32_t zero) {
  asm volatile("{\n.reg .pred p;\n.reg .u32 c;\nSEP_L:\n.pragma \"nounroll\";\nmov.u32 c, %%clock;\nsetp.lt.u32 p, c, %0;\n@p bra SEP_L;\n}\n" :: "r"(zero) : "memory");
}
__device__ __forceinline__ void wg_fence() { asm volatile("wgmma.fence.sync.aligned;" ::: "memory"); }
__device__ __forceinline__ void wg_commit() { asm volatile("wgmma.commit_group.sync.aligned;" ::: "memory"); }
template<int N> __device__ __forceinline__ void wg_wait() { asm volatile("wgmma.wait_group.sync.aligned %0;" :: "n"(N) : "memory"); }
__device__ __forceinline__ void fence_regs(float (&d)[72]) {
  #pragma unroll
  for (int i = 0; i < 72; i++) asm volatile("" : "+f"(d[i]) :: "memory");
}
__device__ __forceinline__ void fence_async_smem() { asm volatile("fence.proxy.async.shared::cta;" ::: "memory"); }
template<int ID, int N> __device__ __forceinline__ void bar_sync() { asm volatile("bar.sync %0, %1;" :: "n"(ID), "n"(N) : "memory"); }
template<int ID, int N> __device__ __forceinline__ void bar_arrive() { asm volatile("bar.arrive %0, %1;" :: "n"(ID), "n"(N) : "memory"); }
__device__ __forceinline__ void cluster_sync() {
  asm volatile("barrier.cluster.arrive.relaxed.aligned;\nbarrier.cluster.wait.aligned;" ::: "memory");
}
__device__ __forceinline__ uint32_t pack_bf16(float lo, float hi) {
  uint32_t r; asm("cvt.rn.bf16x2.f32 %0, %1, %2;" : "=r"(r) : "f"(hi), "f"(lo)); return r;
}
__device__ __forceinline__ uint32_t max_bf16x2(uint32_t a, uint32_t b) {
  uint32_t r; asm("max.bf16x2 %0, %1, %2;" : "=r"(r) : "r"(a), "r"(b)); return r;
}
__device__ __forceinline__ uint32_t add_bf16x2(uint32_t a, uint32_t b) {
  uint32_t r; asm("add.rn.bf16x2 %0, %1, %2;" : "=r"(r) : "r"(a), "r"(b)); return r;
}
__device__ __forceinline__ uint32_t sub_bf16x2(uint32_t a, uint32_t b) {
  uint32_t r; asm("sub.rn.bf16x2 %0, %1, %2;" : "=r"(r) : "r"(a), "r"(b)); return r;
}
__device__ __forceinline__ uint32_t ex2_bf16x2(uint32_t a) {
  uint32_t r;
  asm("{\n.reg .b32 t;\nex2.approx.ftz.bf16x2 t, %1;\nmax.NaN.bf16x2 %0, t, %2;\n}\n" : "=r"(r) : "r"(a), "r"(0u));
  return r;
}
__device__ __forceinline__ void ex2_halves(uint32_t a, uint16_t& lo, uint16_t& hi) {
  asm volatile("{\n.reg .b16 l, h;\nmov.b32 {l, h}, %2;\nex2.approx.ftz.bf16 %0, l;\nex2.approx.ftz.bf16 %1, h;\n}\n" : "=h"(lo), "=h"(hi) : "r"(a));
}
__device__ __forceinline__ uint32_t pack_halves(uint16_t lo, uint16_t hi) {
  uint32_t r; asm volatile("mov.b32 %0, {%1, %2};" : "=r"(r) : "h"(lo), "h"(hi)); return r;
}
__device__ __forceinline__ uint32_t pack_halves_pin(uint16_t lo, uint16_t hi) {
  uint32_t r; asm volatile("{\n.reg .b32 t;\nmov.b32 t, {%1, %2};\nmax.NaN.bf16x2 %0, t, %3;\n}\n" : "=r"(r) : "h"(lo), "h"(hi), "r"(0u)); return r;
}
__device__ __forceinline__ float bf_lo(uint32_t v) { return __uint_as_float(v << 16); }
__device__ __forceinline__ float bf_hi(uint32_t v) { return __uint_as_float(v & 0xffff0000u); }
__device__ __forceinline__ void ldsm4t(uint32_t addr, uint32_t& a, uint32_t& b, uint32_t& c, uint32_t& d) {
  asm volatile("ldmatrix.sync.aligned.m8n8.x4.trans.shared.b16 {%0, %1, %2, %3}, [%4];"
    : "=r"(a), "=r"(b), "=r"(c), "=r"(d) : "r"(addr));
}
__device__ __forceinline__ void stsm4t(uint32_t addr, uint32_t a, uint32_t b, uint32_t c, uint32_t d) {
  asm volatile("stmatrix.sync.aligned.m8n8.x4.trans.shared.b16 [%0], {%1, %2, %3, %4};"
    :: "r"(addr), "r"(a), "r"(b), "r"(c), "r"(d));
}
__device__ __forceinline__ float4 lds128(uint32_t addr) {
  float4 v; asm volatile("ld.shared.v4.f32 {%0, %1, %2, %3}, [%4];" : "=f"(v.x), "=f"(v.y), "=f"(v.z), "=f"(v.w) : "r"(addr)); return v;
}
__device__ __forceinline__ void sts32(uint32_t addr, uint32_t v) { asm volatile("st.shared.u32 [%0], %1;" :: "r"(addr), "r"(v) : "memory"); }
__device__ __forceinline__ void red_max_f32(uint32_t addr, float v, bool on) {
  asm volatile("{\n.reg .pred p, q, e;\nsetp.ne.b32 e, %2, 0;\nsetp.ge.and.s32 p|q, %1, 0, e;\n"
               "@p red.shared.max.s32 [%0], %1;\n@q red.shared.min.u32 [%0], %1;\n}\n"
               :: "r"(addr), "r"(__float_as_uint(v)), "r"((uint32_t)on) : "memory");
}

#define ACC_REGS "{%0, %1, %2, %3, %4, %5, %6, %7, %8, %9, %10, %11, %12, %13, %14, %15, %16, %17, %18, %19, %20, %21, %22, %23, %24, %25, %26, %27, %28, %29, %30, %31, %32, %33, %34, %35, %36, %37, %38, %39, %40, %41, %42, %43, %44, %45, %46, %47, %48, %49, %50, %51, %52, %53, %54, %55, %56, %57, %58, %59, %60, %61, %62, %63, %64, %65, %66, %67, %68, %69, %70, %71}"
template<int TA, int OA, int OB>
__device__ __forceinline__ void mma(float (&d)[72], uint32_t a, uint32_t b) {
  asm volatile("{\n.reg .b64 da, db;\n.reg .b32 ta, tb, th;\n"
    "add.u32 ta, %72, %75;\nadd.u32 tb, %73, %76;\nmov.b32 th, 0x40000040;\n"
    "mov.b64 da, {ta, th};\nmov.b64 db, {tb, th};\n"
    "wgmma.mma_async.sync.aligned.m64n144k16.f32.bf16.bf16 " ACC_REGS ", da, db, 1, 1, 1, %74, 0;\n}\n"
    : "+f"(d[0]), "+f"(d[1]), "+f"(d[2]), "+f"(d[3]), "+f"(d[4]), "+f"(d[5]), "+f"(d[6]), "+f"(d[7]), "+f"(d[8]), "+f"(d[9]), "+f"(d[10]), "+f"(d[11]),
      "+f"(d[12]), "+f"(d[13]), "+f"(d[14]), "+f"(d[15]), "+f"(d[16]), "+f"(d[17]), "+f"(d[18]), "+f"(d[19]), "+f"(d[20]), "+f"(d[21]), "+f"(d[22]), "+f"(d[23]),
      "+f"(d[24]), "+f"(d[25]), "+f"(d[26]), "+f"(d[27]), "+f"(d[28]), "+f"(d[29]), "+f"(d[30]), "+f"(d[31]), "+f"(d[32]), "+f"(d[33]), "+f"(d[34]), "+f"(d[35]),
      "+f"(d[36]), "+f"(d[37]), "+f"(d[38]), "+f"(d[39]), "+f"(d[40]), "+f"(d[41]), "+f"(d[42]), "+f"(d[43]), "+f"(d[44]), "+f"(d[45]), "+f"(d[46]), "+f"(d[47]),
      "+f"(d[48]), "+f"(d[49]), "+f"(d[50]), "+f"(d[51]), "+f"(d[52]), "+f"(d[53]), "+f"(d[54]), "+f"(d[55]), "+f"(d[56]), "+f"(d[57]), "+f"(d[58]), "+f"(d[59]),
      "+f"(d[60]), "+f"(d[61]), "+f"(d[62]), "+f"(d[63]), "+f"(d[64]), "+f"(d[65]), "+f"(d[66]), "+f"(d[67]), "+f"(d[68]), "+f"(d[69]), "+f"(d[70]), "+f"(d[71])
    : "r"(a), "r"(b), "n"(TA), "n"(OA / 16), "n"(OB / 16));
}
template<int TA, int OA, int OB>
__device__ __forceinline__ void mma_init(float (&d)[72], uint32_t a, uint32_t b) {
  asm volatile("{\n.reg .b64 da, db;\n.reg .b32 ta, tb, th;\n"
    "add.u32 ta, %72, %75;\nadd.u32 tb, %73, %76;\nmov.b32 th, 0x40000040;\n"
    "mov.b64 da, {ta, th};\nmov.b64 db, {tb, th};\n"
    "wgmma.mma_async.sync.aligned.m64n144k16.f32.bf16.bf16 " ACC_REGS ", da, db, 0, 1, 1, %74, 0;\n}\n"
    : "=f"(d[0]), "=f"(d[1]), "=f"(d[2]), "=f"(d[3]), "=f"(d[4]), "=f"(d[5]), "=f"(d[6]), "=f"(d[7]), "=f"(d[8]), "=f"(d[9]), "=f"(d[10]), "=f"(d[11]),
      "=f"(d[12]), "=f"(d[13]), "=f"(d[14]), "=f"(d[15]), "=f"(d[16]), "=f"(d[17]), "=f"(d[18]), "=f"(d[19]), "=f"(d[20]), "=f"(d[21]), "=f"(d[22]), "=f"(d[23]),
      "=f"(d[24]), "=f"(d[25]), "=f"(d[26]), "=f"(d[27]), "=f"(d[28]), "=f"(d[29]), "=f"(d[30]), "=f"(d[31]), "=f"(d[32]), "=f"(d[33]), "=f"(d[34]), "=f"(d[35]),
      "=f"(d[36]), "=f"(d[37]), "=f"(d[38]), "=f"(d[39]), "=f"(d[40]), "=f"(d[41]), "=f"(d[42]), "=f"(d[43]), "=f"(d[44]), "=f"(d[45]), "=f"(d[46]), "=f"(d[47]),
      "=f"(d[48]), "=f"(d[49]), "=f"(d[50]), "=f"(d[51]), "=f"(d[52]), "=f"(d[53]), "=f"(d[54]), "=f"(d[55]), "=f"(d[56]), "=f"(d[57]), "=f"(d[58]), "=f"(d[59]),
      "=f"(d[60]), "=f"(d[61]), "=f"(d[62]), "=f"(d[63]), "=f"(d[64]), "=f"(d[65]), "=f"(d[66]), "=f"(d[67]), "=f"(d[68]), "=f"(d[69]), "=f"(d[70]), "=f"(d[71])
    : "r"(a), "r"(b), "n"(TA), "n"(OA / 16), "n"(OB / 16));
}
template<int OB>
__device__ __forceinline__ void mma_rs(float (&d)[72], uint32_t diag, uint32_t b) {
  asm volatile("{\n.reg .b64 db;\n.reg .b32 tb, th, z;\n"
    "add.u32 tb, %73, %74;\nmov.b32 th, 0x40000040;\nmov.b32 z, 0;\nmov.b64 db, {tb, th};\n"
    "wgmma.mma_async.sync.aligned.m64n144k16.f32.bf16.bf16 " ACC_REGS ", {%72, z, z, %72}, db, 1, 1, 1, 0;\n}\n"
    : "+f"(d[0]), "+f"(d[1]), "+f"(d[2]), "+f"(d[3]), "+f"(d[4]), "+f"(d[5]), "+f"(d[6]), "+f"(d[7]), "+f"(d[8]), "+f"(d[9]), "+f"(d[10]), "+f"(d[11]),
      "+f"(d[12]), "+f"(d[13]), "+f"(d[14]), "+f"(d[15]), "+f"(d[16]), "+f"(d[17]), "+f"(d[18]), "+f"(d[19]), "+f"(d[20]), "+f"(d[21]), "+f"(d[22]), "+f"(d[23]),
      "+f"(d[24]), "+f"(d[25]), "+f"(d[26]), "+f"(d[27]), "+f"(d[28]), "+f"(d[29]), "+f"(d[30]), "+f"(d[31]), "+f"(d[32]), "+f"(d[33]), "+f"(d[34]), "+f"(d[35]),
      "+f"(d[36]), "+f"(d[37]), "+f"(d[38]), "+f"(d[39]), "+f"(d[40]), "+f"(d[41]), "+f"(d[42]), "+f"(d[43]), "+f"(d[44]), "+f"(d[45]), "+f"(d[46]), "+f"(d[47]),
      "+f"(d[48]), "+f"(d[49]), "+f"(d[50]), "+f"(d[51]), "+f"(d[52]), "+f"(d[53]), "+f"(d[54]), "+f"(d[55]), "+f"(d[56]), "+f"(d[57]), "+f"(d[58]), "+f"(d[59]),
      "+f"(d[60]), "+f"(d[61]), "+f"(d[62]), "+f"(d[63]), "+f"(d[64]), "+f"(d[65]), "+f"(d[66]), "+f"(d[67]), "+f"(d[68]), "+f"(d[69]), "+f"(d[70]), "+f"(d[71])
    : "r"(diag), "r"(b), "n"(OB / 16));
}

__device__ __forceinline__ void store_acc_T(const float (&d)[72], uint32_t addr) {
  #pragma unroll
  for (int j = 0; j < 18; j += 2)
    stsm4t(addr + j * 1024, pack_bf16(d[4*j], d[4*j+1]), pack_bf16(d[4*j+2], d[4*j+3]),
           pack_bf16(d[4*j+4], d[4*j+5]), pack_bf16(d[4*j+6], d[4*j+7]));
}

template<bool IS_MAX>
__device__ __forceinline__ void warp_col_reduce(const uint32_t (&v)[18], uint32_t (&r3)[3], int lane) {
  #define OP(a, b) (IS_MAX ? max_bf16x2(a, b) : add_bf16x2(a, b))
  const bool b4 = lane & 16, b3 = lane & 8, b2 = lane & 4;
  uint32_t r1[9], r2[5];
  #pragma unroll
  for (int k = 0; k < 9; k++) {
    const uint32_t snd = b4 ? v[k] : v[k+9], kp = b4 ? v[k+9] : v[k];
    r1[k] = OP(kp, __shfl_xor_sync(0xffffffff, snd, 16));
  }
  #pragma unroll
  for (int k = 0; k < 4; k++) {
    const uint32_t snd = b3 ? r1[k] : r1[k+4], kp = b3 ? r1[k+4] : r1[k];
    r2[k] = OP(kp, __shfl_xor_sync(0xffffffff, snd, 8));
  }
  r2[4] = OP(r1[8], __shfl_xor_sync(0xffffffff, r1[8], 8));
  #pragma unroll
  for (int k = 0; k < 2; k++) {
    const uint32_t snd = b2 ? r2[k] : r2[k+2], kp = b2 ? r2[k+2] : r2[k];
    r3[k] = OP(kp, __shfl_xor_sync(0xffffffff, snd, 4));
  }
  r3[2] = OP(r2[4], __shfl_xor_sync(0xffffffff, r2[4], 4));
  #undef OP
}

constexpr uint32_t XLAP = 0x12435u, GLAP0 = 0x53241u, GLAP = 0x54321u;
struct Seg { int isq, head_or_k0, n, np; uint32_t lap, lap2; int lap0; };
__device__ __forceinline__ Seg seg_info(int n, int sh) {
  Seg s;
  s.isq = n <= 4 - sh;
  s.head_or_k0 = n == 0 ? 3 : (s.isq ? n - 1 : (n - 5 + sh) * 16);
  s.np = n == 6 ? 1 + sh : 0;
  s.n = n == 6 ? 49 - 15 * sh : 16;
  const bool g = n >= 2 && n <= 5;
  s.lap = g ? GLAP0 : XLAP;
  s.lap2 = g ? GLAP : XLAP;
  s.lap0 = n == 0 ? 4 : 0;
  return s;
}

__global__ void __launch_bounds__(384, 1) fused_kernel(const __grid_constant__ Params P) {
  extern __shared__ __align__(1024) char smem_raw[];
  const uint32_t sb = (smem_u32(smem_raw) + 1023u) & ~1023u;
  const uint32_t full0 = sb + OFF_BAR;
  const uint32_t emptyB = full0 + 48;
  const uint32_t emptyA = full0 + 192;
  const uint32_t stg0 = full0 + 96, maxbar = full0 + 104, stgfree = full0 + 112, ordy = full0 + 144;
  const uint32_t kvcnt = full0 + 128;
  const int tid = threadIdx.x;
  const int wg = __shfl_sync(0xffffffff, tid >> 7, 0);
  uint32_t rank; asm volatile("mov.u32 %0, %%cluster_ctarank;" : "=r"(rank));
  int cl;
  {
    const int c = blockIdx.x >> 1, t = c - 4;
    int set, idx;
    if (c < 4) { set = 1; idx = c; }
    else if (t < 32) { set = 2 * (t & 7); idx = t >> 3; }
    else { set = 2 * (1 + (t - 32) % 7) + 1; idx = (t - 32) / 7; }
    cl = set * 4 + idx;
    cl = (cl & 7) | (((cl >> 3) & 1) << 5) | ((cl >> 4) << 3);
  }
  const int blk = cl >> 5, b = cl & 7, sub = ((cl >> 3) & 3) * 2 + rank, sh = blk;
  uint4* const park = g_park + (cl * 2 + rank) * (2 * (PAIR / 16));

  if (tid == 0) {
    for (int i = 0; i < 6; i++) { mbar_init(full0 + 8*i, 1); mbar_init(emptyB + 8*i, 4); mbar_init(emptyA + 8*i, 2); }
    mbar_init(stg0, 8); mbar_init(maxbar, 8); mbar_init(stgfree, 1);
    for (int i = 0; i < 4; i++) mbar_init(ordy + 8*i, 1);
    asm volatile("fence.mbarrier_init.release.cluster;" ::: "memory");
  }
  if (tid < 288) sts32(sb + OFF_MAX + tid * 4, 0xff800000u);
  if (tid == 300) sts32(kvcnt, 0u);
  __syncthreads();
  cluster_sync();

  if (wg == 2) {
    asm volatile("setmaxnreg.dec.sync.aligned.u32 24;");
    const int warp = __shfl_sync(0xffffffff, (tid >> 5) & 3, 0);
    const int lane = tid & 31;
    const uint32_t ebar = warp == 0 ? emptyA : emptyB;
    #define ACQ(s) do { mbar_wait(ebar + 8*(s), (eph >> (s)) & 1); eph ^= 1u << (s); } while (0)
    if (warp == 0) {
      uint32_t eph = 0x3Fu;
      const uint64_t pol = evict_first_policy();
      int nkv = 0;
      uint32_t tlast = (uint32_t)clock64();
      #pragma unroll 1
      for (int n = 1 - sh; n < 7; n++) {
        Seg sg = seg_info(n, sh);
        const CUtensorMap* map = sg.isq ? &P.wq[blk] : &P.wo[blk];
        const int k0 = sg.isq ? 0 : sg.head_or_k0, col = (sg.isq ? sg.head_or_k0 * 8 + sub : sub) * 2;
        int lp = sg.lap0;
        #pragma unroll 1
        for (int j = 0; j < sg.n; j++) {
          const int s = (sg.lap >> (lp * 4)) & 15;
          const int kk = k0 + j - sg.np;
          if (j < sg.np) {
            if (j == 1) { mbar_wait(ordy + 16, 0); ACQ(s); bulk_load_pair(sb + s * PAIR, park, full0 + 8*s); }
          } else {
            ACQ(s);
            tma3d(sb + s * PAIR + SLOT, map, kk * 64, col, full0 + 8*s, 18432 + 16384, pol);
          }
          if (++lp == 5) { lp = 0; sg.lap = sg.lap2; }
        }
        #pragma unroll 1
        for (int q = (n >= 2 && n <= 5 ? 0 : 4); q < (n >= 1 && n <= 4 ? 8 : 4); q++) {
          if (sh && n == 4 && q == 4) { mbar_wait(ordy, 0); ACQ(5); bulk_load_pair(sb + 5 * PAIR, park + PAIR / 16, full0 + 40); }
          const int s = (0x32432432u >> (q * 4)) & 15;
          const int head = (q < 4 ? n - 2 : n - 1) * 8 + sub;
          ACQ(s);
          { const int gap = (q == 1 || q == 2) ? 1300 : 0;
            while ((int)((uint32_t)clock64() - tlast) < gap) __nanosleep(30);
            tlast = (uint32_t)clock64(); }
          tma3d(sb + s * PAIR, q < 4 ? &P.v[blk] : &P.k[blk], (b * 32 + head) * 512 + ((q < 4 ? q : q + 1) & 3) * 128, 0, full0 + 8*s, 32768, pol);
          nkv++;
          asm volatile("st.volatile.shared.u32 [%0], %1;" :: "r"(kvcnt), "r"(nkv) : "memory");
        }
      }
    } else if (warp == 1) {
      uint32_t eph = 0x3Fu;
      #pragma unroll 1
      for (int n = 1 - sh; n < 7; n++) {
        Seg sg = seg_info(n, sh);
        const CUtensorMap* map = sg.isq ? &P.x[blk] : &P.os;
        const int row = (sg.isq ? 0 : blk * TOK) + b * SQ + rank * 72, k0 = sg.isq ? 0 : sg.head_or_k0;
        int lp = sg.lap0;
        #pragma unroll 1
        for (int j = 0; j < sg.n; j++) {
          const int s = (sg.lap >> (lp * 4)) & 15;
          if (j >= sg.np) {
            const int kk = k0 + j - sg.np;
            if (!sg.isq && (kk & 15) == 0) mbar_wait(ordy + 8 * (kk >> 4), 0);
            ACQ(s);
            tma2d_mc(sb + s * PAIR + rank * 9216, map, kk * 64, row, full0 + 8*s);
          }
          if (++lp == 5) { lp = 0; sg.lap = sg.lap2; }
        }
      }
    } else if (warp == 2) {
      uint32_t ph = 0;
      #define PARK_STORE(slot, pair) do { if (lane == 0) { mbar_wait(stg0, ph); \
          _Pragma("unroll 1") for (int pc = 0; pc < 12; pc++) \
            asm volatile("cp.async.bulk.global.shared::cta.bulk_group [%0], [%1], %2;" :: "l"(park + (slot) * (PAIR / 16) + pc * 192), "r"(sb + (pair) * PAIR + pc * 3072), "r"(3072) : "memory"); \
          asm volatile("cp.async.bulk.commit_group;" ::: "memory"); \
          asm volatile("cp.async.bulk.wait_group.read 0;" ::: "memory"); \
          if (pair) mbar_arrive(emptyA + 40, 2); else mbar_arrive(stgfree); } \
          ph ^= 1; __syncwarp(); } while (0)
      if (sh) PARK_STORE(1, 0);
      #pragma unroll 1
      for (int n = 0; n < 4; n++) {
        if (n == 2 && sh) PARK_STORE(0, 5);
        bar_sync<4, 288>();
        #pragma unroll
        for (int r = 0; r < 3; r++) {
          const int idx = r * 32 + lane;
          if (idx < 72) {
            float s0 = 0.f, s1 = 0.f;
            #pragma unroll
            for (int ww = 0; ww < 8; ww++) {
              uint32_t v; asm volatile("ld.shared.u32 %0, [%1];" : "=r"(v) : "r"(sb + OFF_SUM + ww * 288 + idx * 4));
              s0 += bf_lo(v); s1 += bf_hi(v);
            }
            asm volatile("st.shared.v2.f32 [%0], {%1, %2};" :: "r"(sb + OFF_INV + idx * 8), "f"(__fdividef(1.f, s0)), "f"(__fdividef(1.f, s1)) : "memory");
          }
        }
        bar_arrive<7, 160>();
        bar_arrive<8, 160>();
        if (lane == 0) {
          mbar_wait(stg0, ph);
          #pragma unroll 1
          for (int pc = 0; pc < 12; pc++)
            tma2d_store(&P.oss, (n * 8 + sub) * 128 + (pc & 1) * 64, blk * TOK + b * SQ + (pc >> 1) * 24, sb + (pc & 1) * SLOT + (pc >> 1) * 3072);
          asm volatile("cp.async.bulk.commit_group;" ::: "memory");
          asm volatile("cp.async.bulk.wait_group.read 0;" ::: "memory");
          mbar_arrive(stgfree);
          asm volatile("cp.async.bulk.wait_group 0;" ::: "memory");
          asm volatile("fence.proxy.async.global;" ::: "memory");
          asm volatile("red.release.gpu.global.add.u32 [%0], %1;" :: "l"(&g_cnt[(blk * 8 + b) * 4 + n]), "r"(1u) : "memory");
        }
        ph ^= 1;
        __syncwarp();
      }
      if (lane == 0) {
        mbar_wait(stg0, ph);
        tma2d_store(&P.out, blk * 1024 + sub * 128, b * SQ, sb);
        tma2d_store(&P.out, blk * 1024 + sub * 128 + 64, b * SQ, sb + SLOT);
        asm volatile("cp.async.bulk.commit_group;" ::: "memory");
        asm volatile("cp.async.bulk.wait_group.read 0;" ::: "memory");
      }
    } else {
      unsigned int epoch;
      asm volatile("ld.relaxed.gpu.global.u32 %0, [%1];" : "=r"(epoch) : "l"(&g_done) : "memory");
      const unsigned int target = 8u * ((epoch >> 7) + 1);
      {
        const char* kp = P.kptr[blk] + (size_t)(b * 32 + sub) * (512 * 256) + lane * 256;
        uint32_t v0 = 0, v1 = 0;
        uint32_t tnext = (uint32_t)clock64() + 2000;
        int q = 0;
        #pragma unroll 1
        for (int spin = 0; spin < 1000000 && q < 8; spin++) {
          int cnt; asm volatile("ld.volatile.shared.u32 %0, [%1];" : "=r"(cnt) : "r"(kvcnt) : "memory");
          if (q < cnt * 2) q = cnt * 2;
          const uint32_t now = (uint32_t)clock64();
          if ((int)(now - tnext) >= 0 && q < 8) {
            const char* a = kp + ((q + 2) & 7) * 16384;
            asm volatile("st.volatile.shared.u32 [%0], %1;" :: "r"(kvcnt + 8), "r"(v0 ^ v1) : "memory");
            asm volatile("ld.global.L2::256B.u32 %0, [%1];" : "=r"(v0) : "l"(a) : "memory");
            asm volatile("ld.global.L2::256B.u32 %0, [%1];" : "=r"(v1) : "l"(a + 8192) : "memory");
            q++; tnext = now + 1400;
          } else __nanosleep(50);
        }
        asm volatile("st.volatile.shared.u32 [%0], %1;" :: "r"(kvcnt + 8), "r"(v0 ^ v1) : "memory");
      }
      int nrdy = 0;
      #pragma unroll 1
      for (int spin = 0; spin < 1000000 && nrdy < 4; spin++) {
        int cnt; asm volatile("ld.volatile.shared.u32 %0, [%1];" : "=r"(cnt) : "r"(kvcnt) : "memory");
        if (cnt >= nrdy * 8 + 8) {
          unsigned int c; asm volatile("ld.acquire.gpu.global.u32 %0, [%1];" : "=r"(c) : "l"(&g_cnt[(blk * 8 + b) * 4 + nrdy]) : "memory");
          if ((int)(c - target) >= 0) {
            asm volatile("fence.proxy.async.global;" ::: "memory");
            __syncwarp();
            if (lane == 0) mbar_arrive(ordy + 8 * nrdy);
            nrdy++;
          }
        }
        __nanosleep(100);
      }
      if (lane == 0) atomicAdd(&g_done, 1u);
    }
    __syncwarp();
    cluster_sync();
  } else {
    asm volatile("setmaxnreg.inc.sync.aligned.u32 240;");
    const int w = wg;
    int t128 = tid & 127;
    asm volatile("" : "+r"(t128));
    #define lane (t128 & 31)
    #define warp (t128 >> 5)
    const uint32_t st_base = sb + w * SLOT + (uint32_t)(((lane >> 4) * 8 + (lane & 7)) * 128 + (((2 * warp + ((lane >> 3) & 1)) ^ (lane & 7)) << 4));
    const uint32_t d0 = ((sb & 0x3FFFF) >> 4) | (64u << 16);
    const uint32_t d0w = d0 + w * 512, d0v = d0 + w * 1024;
    uint32_t rel_addr; asm("mapa.shared::cluster.u32 %0, %1, %2;" : "=r"(rel_addr) : "r"(t128 == 0 ? emptyA : emptyB), "r"(t128 == 0 ? rank : (uint32_t)(t128 & 1)));
    #define WAITF(s, flip) mbar_wait(full0 + 8*(s), ((fph >> (s)) & 1) ^ (flip))
    #define RELX(s, all) asm volatile("{\n.reg .pred p;\nsetp.lt.u32 p, %1, %2;\n@p mbarrier.arrive.relaxed.cluster.shared::cluster.b64 _, [%0];\n}\n" :: "r"(rel_addr + 8*(s)), "r"(t128), "r"((all) ? 3 : 1) : "memory")
    #define REL(s) RELX(s, true)
    #define STG_ARRIVE() do { fence_async_smem(); __syncwarp(); if (lane == 0) mbar_arrive(stg0); } while (0)
    #define STG_FREE() do { mbar_wait(stgfree, sfp); sfp ^= 1; } while (0)
    #define TURN_WAIT() do { if (w) bar_sync<6, 256>(); else bar_sync<5, 256>(); } while (0)
    #define TURN_PASS() do { if (w) bar_arrive<5, 256>(); else bar_arrive<6, 256>(); } while (0)
    #define GMMA(acc, da, db, O, first) do { if (!(first)) fence_regs(acc); wg_fence(); \
        if (first) mma_init<1, (O) + SLOT, (O)>(acc, da, db); else mma<1, (O) + SLOT, (O)>(acc, da, db); \
        mma<1, (O) + SLOT + 2048, (O) + 32>(acc, da, db); mma<1, (O) + SLOT + 4096, (O) + 64>(acc, da, db); \
        mma<1, (O) + SLOT + 6144, (O) + 96>(acc, da, db); wg_commit(); } while (0)
    const float cs = 0.08838834764831845f * 1.4426950408889634f;
    uint32_t fph = 0, sfp = 0;
    #define XLOOP(a0, j0, n, lp0, tail_local) do { int lp = lp0; \
        _Pragma("unroll 1") for (int j = j0; j < n; j++) { \
          const int s_ = (XLAP >> (lp * 4)) & 15; \
          WAITF(s_, 0); fph ^= 1u << s_; \
          const uint32_t off = s_ * (PAIR / 16); \
          GMMA(a0, d0w + off, d0 + off, 0, false); \
          wg_wait<1>(); \
          if (j > j0) RELX(sprev, !((tail_local) && j > n - 5 && sprev >= 2 && sprev <= 4)); \
          sprev = s_; \
          if (++lp == 5) lp = 0; \
        } } while (0)
    #pragma unroll 1
    for (int h = -sh; h <= 0; h++) {
      float a0[72];
      #pragma unroll
      for (int i = 0; i < 72; i++) a0[i] = 0.f;
      int sprev = 0;
      XLOOP(a0, 0, 16, h ? 4 : 0, h == 0);
      wg_wait<0>();
      fence_regs(a0);
      if (h == 0) bar_sync<3, 256>(); else REL(sprev);
      #pragma unroll
      for (int i = 0; i < 72; i++) a0[i] *= cs;
      store_acc_T(a0, st_base + (h == 0 ? 5 * PAIR : 0));
      fence_async_smem();
      if (h != 0) { __syncwarp(); if (lane == 0) mbar_arrive(stg0); }
    }
    if (w) bar_arrive<5, 256>();
    uint32_t sp[3][36];
    uint32_t mx[18];
        #define PACK(s, i) do { _Pragma("unroll") for (int j = 0; j < 18; j++) { \
            sp[i][2*j] = pack_bf16(s[4*j], s[4*j+1]); sp[i][2*j+1] = pack_bf16(s[4*j+2], s[4*j+3]); \
            const uint32_t m2 = max_bf16x2(sp[i][2*j], sp[i][2*j+1]); \
            mx[j] = (i) ? max_bf16x2(mx[j], m2) : m2; \
            asm volatile("" : "+r"(sp[i][2*j]), "+r"(sp[i][2*j+1]), "+r"(mx[j]) :: "memory"); } } while (0)
        #define SISSUE(s, p, fin) do { TURN_WAIT(); wg_fence(); \
            mma_init<0, (p) * PAIR, 5 * PAIR>(s, d0w, d0);      mma<0, (p) * PAIR + 32, 5 * PAIR + 32>(s, d0w, d0); \
            mma<0, (p) * PAIR + 64, 5 * PAIR + 64>(s, d0w, d0); mma<0, (p) * PAIR + 96, 5 * PAIR + 96>(s, d0w, d0); \
            mma<0, (p) * PAIR + 16384, 5 * PAIR + SLOT>(s, d0w, d0);           mma<0, (p) * PAIR + 16384 + 32, 5 * PAIR + SLOT + 32>(s, d0w, d0); \
            mma<0, (p) * PAIR + 16384 + 64, 5 * PAIR + SLOT + 64>(s, d0w, d0); mma<0, (p) * PAIR + 16384 + 96, 5 * PAIR + SLOT + 96>(s, d0w, d0); \
            wg_commit(); if (!(fin) || !w) TURN_PASS(); } while (0)
    #define O_NORM_STSM() do { _Pragma("unroll") for (int c_ = 0; c_ < 9; c_++) \
        stsm4t(st_base + c_ * 2048, pack_bf16(o[8*c_] * iv[c_].x, o[8*c_+1] * iv[c_].y), pack_bf16(o[8*c_+2] * iv[c_].x, o[8*c_+3] * iv[c_].y), \
               pack_bf16(o[8*c_+4] * iv[c_].z, o[8*c_+5] * iv[c_].w), pack_bf16(o[8*c_+6] * iv[c_].z, o[8*c_+7] * iv[c_].w)); } while (0)
    #define PHASE_S(with_o, wait_stg) do { \
        float sa[72], sc[72], s[72]; \
        WAITF(3, 0); \
        SISSUE(sa, 3, false); \
        with_o; \
        wg_wait<0>(); fence_regs(sa); RELX(3, false); \
        WAITF(4, 0); \
        SISSUE(sc, 4, false); \
        sched_sep(P.zero); \
        PACK(sa, 0); \
        if (sizeof(#with_o) > 1) STG_ARRIVE(); \
        sched_sep(P.zero); \
        wg_wait<0>(); fence_regs(sc); REL(4); \
        PACK(sc, 1); \
        WAITF(2, 0); \
        SISSUE(sc, 2, false); \
        wg_wait<0>(); fence_regs(sc); REL(2); \
        PACK(sc, 2); \
        WAITF(3, 1); \
        SISSUE(s, 3, true); \
        wg_wait<0>(); fence_regs(s); REL(3); REL(5); \
        if (wait_stg) STG_FREE(); \
        _Pragma("unroll") for (int c = 0; c < 9; c++) { \
          const uint32_t k0 = pack_bf16(s[8*c], s[8*c+1]), k1 = pack_bf16(s[8*c+2], s[8*c+3]); \
          const uint32_t k2 = pack_bf16(s[8*c+4], s[8*c+5]), k3 = pack_bf16(s[8*c+6], s[8*c+7]); \
          stsm4t(st_base + c * 2048, k0, k1, k2, k3); \
          mx[2*c] = max_bf16x2(mx[2*c], max_bf16x2(k0, k1)); \
          mx[2*c+1] = max_bf16x2(mx[2*c+1], max_bf16x2(k2, k3)); \
          asm volatile("" : "+r"(mx[2*c]), "+r"(mx[2*c+1]) :: "memory"); \
        } \
        fph ^= 0x14u; } while (0)
    PHASE_S(, sh);
    #pragma unroll 1
    for (int h = 0; ; h++) {
      const uint32_t hodd = h & 1;
      const bool last = h == 3, gq = h + sh < 3;
      const uint32_t ma = sb + OFF_MAX + hodd * 576 + (lane & 3) * 144;
      uint32_t l2[18];
      {
        float a0[72];
        #define U0(j) ((j) <= 2 ? 0 : ((j) >= 16 ? 27 : (((j) - 2) * 27) / 14))
        uint32_t mm[2][2], pk[2][4];
        float4 mr;
        uint16_t eh[2][8];
        #define GP(j) ((j) < 0 ? 1 : ((j) < 5 ? (int)((GLAP0 >> (((j) & 7) * 4)) & 15) : 1 + (j) % 5))
        #define GSTEP(j) do { \
          WAITF(GP(j), ((j) / 5) & 1); \
          if ((j) > 0) { wg_wait<0>(); if ((j) < 15) RELX(GP((j) - 1), (j) < 12); } \
          if ((j) == 1) mbar_wait(maxbar, hodd); \
          GMEM(j); \
          GMMA(a0, d0w, d0, GP(j) * PAIR, (j) == 0); \
          if ((j) == 0) { \
            uint32_t r3[3]; warp_col_reduce<true>(mx, r3, lane); \
            const int jb = (lane & 16) ? 9 : 0, j0 = jb + ((lane & 8) ? 4 : 0) + ((lane & 4) ? 2 : 0); \
            red_max_f32(ma + j0 * 8, bf_lo(r3[0]), true);      red_max_f32(ma + j0 * 8 + 4, bf_hi(r3[0]), true); \
            red_max_f32(ma + j0 * 8 + 8, bf_lo(r3[1]), true);  red_max_f32(ma + j0 * 8 + 12, bf_hi(r3[1]), true); \
            red_max_f32(ma + (jb + 8) * 8, bf_lo(r3[2]), !(lane & 12)); red_max_f32(ma + (jb + 8) * 8 + 4, bf_hi(r3[2]), !(lane & 12)); \
            __syncwarp(); if (lane == 0) mbar_arrive(maxbar); } \
          GEXP(j); } while (0)
        #define GMEM(j) do { \
          _Pragma("unroll") for (int u = U0(j); u < U0((j) + 1); u++) if (u % 3 == 0) { \
            mm[(u / 3) & 1][0] = __byte_perm(__float_as_uint(mr.x), __float_as_uint(mr.y), 0x7632); \
            mm[(u / 3) & 1][1] = __byte_perm(__float_as_uint(mr.z), __float_as_uint(mr.w), 0x7632); } \
          _Pragma("unroll") for (int u = U0((j) - 1); u < U0(j); u++) if (u % 3 == 0) { \
            const int c = u / 3; uint16_t (&e)[8] = eh[u - U0((j) - 1)]; \
            const uint32_t k0 = pack_halves(e[0], e[1]), k1 = pack_halves(e[2], e[3]), k2 = pack_halves(e[4], e[5]), k3 = pack_halves(e[6], e[7]); \
            stsm4t(st_base + c * 2048, k0, k1, k2, k3); \
            l2[2*c] = add_bf16x2(k0, k1); l2[2*c+1] = add_bf16x2(k2, k3); asm volatile("" : "+r"(l2[2*c]), "+r"(l2[2*c+1])); } \
          _Pragma("unroll") for (int u = U0((j) + 1); u < U0((j) + 2); u++) if (u % 3 == 0) { \
            const int c = u / 3; \
            mr = lds128(ma + c * 16); \
            ldsm4t(st_base + c * 2048, pk[c & 1][0], pk[c & 1][1], pk[c & 1][2], pk[c & 1][3]); \
          } } while (0)
        #define GEXP(j) do { \
          _Pragma("unroll") for (int u = U0((j) - 1); u < U0(j); u++) if (u % 3) { \
            const int c = u / 3, t = u % 3; uint16_t (&e)[8] = eh[u - U0((j) - 1)]; \
            uint32_t (&q)[36] = sp[t ? t - 1 : 0]; \
            q[4*c] = pack_halves_pin(e[0], e[1]); q[4*c+1] = pack_halves_pin(e[2], e[3]); \
            q[4*c+2] = pack_halves_pin(e[4], e[5]); q[4*c+3] = pack_halves_pin(e[6], e[7]); \
            l2[2*c] = add_bf16x2(l2[2*c], add_bf16x2(q[4*c], q[4*c+1])); l2[2*c+1] = add_bf16x2(l2[2*c+1], add_bf16x2(q[4*c+2], q[4*c+3])); \
            asm volatile("" : "+r"(l2[2*c]), "+r"(l2[2*c+1])); \
          } \
          _Pragma("unroll") for (int u = U0(j); u < U0((j) + 1); u++) { \
            const int c = u / 3, t = u % 3; uint16_t (&e)[8] = eh[u - U0(j)]; \
            const uint32_t* q = t ? &sp[t ? t - 1 : 0][4*c] : pk[c & 1]; \
            ex2_halves(sub_bf16x2(q[0], mm[c & 1][0]), e[0], e[1]); ex2_halves(sub_bf16x2(q[1], mm[c & 1][0]), e[2], e[3]); \
            ex2_halves(sub_bf16x2(q[2], mm[c & 1][1]), e[4], e[5]); ex2_halves(sub_bf16x2(q[3], mm[c & 1][1]), e[6], e[7]); \
            if (t == 1) { \
              sp[2][4*c] = sub_bf16x2(sp[2][4*c], mm[c & 1][0]); sp[2][4*c+1] = sub_bf16x2(sp[2][4*c+1], mm[c & 1][0]); \
              sp[2][4*c+2] = sub_bf16x2(sp[2][4*c+2], mm[c & 1][1]); sp[2][4*c+3] = sub_bf16x2(sp[2][4*c+3], mm[c & 1][1]); \
              asm volatile("" : "+r"(sp[2][4*c]), "+r"(sp[2][4*c+1]), "+r"(sp[2][4*c+2]), "+r"(sp[2][4*c+3])); } \
          } } while (0)
        GSTEP(0); GSTEP(1); GSTEP(2); GSTEP(3); GSTEP(4); GSTEP(5); GSTEP(6); GSTEP(7);
        GSTEP(8); GSTEP(9); GSTEP(10); GSTEP(11); GSTEP(12); GSTEP(13); GSTEP(14); GSTEP(15);
        fph ^= 0x3Cu;
        WAITF(2, 0);
        GMEM(16); GEXP(16);
        fence_async_smem();
        bar_sync<3, 256>();
        wg_wait<0>();
        fence_regs(a0);
        if (w) bar_arrive<10, 256>();
        if (gq) {
          #pragma unroll
          for (int i = 0; i < 72; i++) a0[i] *= cs;
        }
        store_acc_T(a0, st_base + 5 * PAIR);
        if (!gq && !last) STG_ARRIVE();
      }
      float o[72];
      #define STORE_P(i) do { _Pragma("unroll") for (int c_ = 0; c_ < 9; c_++) \
          stsm4t(st_base + ((i) & 1) * PAIR + c_ * 2048, sp[(i)-1][4*c_], sp[(i)-1][4*c_+1], sp[(i)-1][4*c_+2], sp[(i)-1][4*c_+3]); } while (0)
      #define PVSTEP(i) do { \
        constexpr int v_ = (i) == 3 ? 2 : 2 + (i), pb_ = ((i) & 1) * PAIR; \
        if ((i) > 0) { \
          if (!w) { bar_sync<9 + ((i) & 1), 256>(); STORE_P((i) ? (i) : 1); } \
          if ((i) == 3) { \
            uint32_t r3[3]; \
            warp_col_reduce<false>(l2, r3, lane); \
            const int jb = (lane & 16) ? 9 : 0, j0 = jb + ((lane & 8) ? 4 : 0) + ((lane & 4) ? 2 : 0); \
            const uint32_t sa = sb + OFF_SUM + (w * 4 + warp) * 288 + (lane & 3) * 72; \
            sts32(sa + j0 * 4, r3[0]); sts32(sa + j0 * 4 + 4, r3[1]); sts32(sa + (jb + 8) * 4, r3[2]); \
            if (t128 < 72) sts32(sb + OFF_MAX + (hodd ^ 1) * 576 + w * 288 + t128 * 4, 0xff800000u); \
            bar_arrive<4, 288>(); } \
          wg_wait<0>(); \
          RELX(1 + (i), (i) > 1 && last && !(sh && (i) == 2)); \
          if (w && (i) < 3) bar_arrive<10 - ((i) & 1), 256>(); \
          if (!w) fence_async_smem(); \
          WAITF(v_, (i) == 3); \
        } \
        if (!w) { if ((i) > 0) bar_sync<5, 256>(); } else { \
          bar_sync<6, 256>(); \
          if ((i) < 3) STORE_P((i) < 3 ? (i) + 1 : 1); \
        } \
        if ((i) > 0) fence_regs(o); \
        wg_fence(); \
        if ((i) == 0) mma_init<1, v_ * PAIR, pb_>(o, d0v, d0); else mma<1, v_ * PAIR, pb_>(o, d0v, d0); \
        mma<1, v_ * PAIR + 2048, pb_ + 32>(o, d0v, d0); mma<1, v_ * PAIR + 4096, pb_ + 64>(o, d0v, d0); mma<1, v_ * PAIR + 6144, pb_ + 96>(o, d0v, d0); \
        mma<1, v_ * PAIR + 8192, pb_ + SLOT>(o, d0v, d0);       mma<1, v_ * PAIR + 10240, pb_ + SLOT + 32>(o, d0v, d0); \
        mma<1, v_ * PAIR + 12288, pb_ + SLOT + 64>(o, d0v, d0); mma<1, v_ * PAIR + 14336, pb_ + SLOT + 96>(o, d0v, d0); \
        wg_commit(); \
        if (!w) bar_arrive<6, 256>(); \
        if ((i) < 3) { sched_sep(P.zero); \
            \
          if ((i) < 2) { _Pragma("unroll") for (int r_ = (i) * 18; r_ < (i) * 18 + 18; r_++) { sp[2][r_] = ex2_bf16x2(sp[2][r_]); asm volatile("" : "+r"(sp[2][r_])); } } \
          else { _Pragma("unroll") for (int r_ = 0; r_ < 18; r_++) \
              asm volatile("{\n.reg .b32 t;\nadd.rn.bf16x2 t, %1, %2;\nadd.rn.bf16x2 %0, %0, t;\n}\n" : "+r"(l2[r_]) : "r"(sp[2][2*r_]), "r"(sp[2][2*r_+1])); } \
          sched_sep(P.zero); } \
        if (w) { if ((i) < 3) fence_async_smem(); bar_arrive<5, 256>(); } } while (0)
      PVSTEP(0);
      PVSTEP(1);
      PVSTEP(2);
      PVSTEP(3);
      fph ^= 0x18u;
      wg_wait<0>();
      fence_regs(o);
      RELX(2, last); REL(1);
      #define LOAD_IV() float4 iv[9]; if (w) bar_sync<8, 160>(); else bar_sync<7, 160>(); \
          _Pragma("unroll") for (int j = 0; j < 9; j++) iv[j] = lds128(sb + OFF_INV + (lane & 3) * 144 + j * 16)
      if (last) {
        LOAD_IV();
        if (!w) bar_sync<5, 256>();
        O_NORM_STSM();
        break;
      }
      if (sh && h == 2) { WAITF(5, 0); fph ^= 0x20u; }
      LOAD_IV();
      PHASE_S(sched_sep(P.zero); O_NORM_STSM(); sched_sep(P.zero), true);
    }
    {
      float a0[72];
      #pragma unroll
      for (int i = 0; i < 72; i++) a0[i] = 0.f;
      const uint32_t dg = (lane >> 3) == (lane & 3) ? ((lane & 4) ? 0x3f800000u : 0x00003f80u) : 0u;
      const uint32_t db = d0 + w * (SLOT / 16);
      const uint32_t g0 = warp == 0 ? dg : 0u, g1 = warp == 1 ? dg : 0u, g2 = warp == 2 ? dg : 0u, g3 = warp == 3 ? dg : 0u;
      #define FOLD(p) do { fence_regs(a0); wg_fence(); \
          mma_rs<(p) * PAIR>(a0, g0, db); mma_rs<(p) * PAIR + 32>(a0, g1, db); mma_rs<(p) * PAIR + 64>(a0, g2, db); mma_rs<(p) * PAIR + 96>(a0, g3, db); \
          wg_commit(); } while (0)
      FOLD(5); STG_ARRIVE(); wg_wait<0>(); fence_regs(a0); REL(5);
      if (sh) { WAITF(3, 0); FOLD(3); wg_wait<0>(); fence_regs(a0); REL(3); fph ^= 0x08u; }
      int sprev = 0;
      XLOOP(a0, 0, 48 - 16 * sh, 1 + sh, true);
      STG_FREE();
      wg_wait<0>();
      fence_regs(a0);
      store_acc_T(a0, st_base);
      STG_ARRIVE();
    }
    cluster_sync();
    #undef lane
    #undef warp
  }
}

typedef CUresult (*PFN_enc)(CUtensorMap*, CUtensorMapDataType, cuuint32_t, void*, const cuuint64_t*, const cuuint64_t*,
                            const cuuint32_t*, const cuuint32_t*, CUtensorMapInterleave, CUtensorMapSwizzle,
                            CUtensorMapL2promotion, CUtensorMapFloatOOBfill);

void enc2d(PFN_enc enc, CUtensorMap* m, const void* p, uint64_t cols, uint64_t rows, uint32_t box_rows) {
  cuuint64_t dims[2] = {cols, rows}; cuuint64_t st[1] = {cols * 2};
  cuuint32_t box[2] = {64, box_rows}; cuuint32_t es[2] = {1, 1};
  enc(m, CU_TENSOR_MAP_DATA_TYPE_BFLOAT16, 2, (void*)p, dims, st, box, es, CU_TENSOR_MAP_INTERLEAVE_NONE,
      CU_TENSOR_MAP_SWIZZLE_128B, CU_TENSOR_MAP_L2_PROMOTION_L2_128B, CU_TENSOR_MAP_FLOAT_OOB_FILL_NONE);
}
void enc3d(PFN_enc enc, CUtensorMap* m, const void* p, uint64_t cols, uint64_t rows, uint32_t box_rows) {
  cuuint64_t dims[3] = {64, rows, cols / 64}; cuuint64_t st[2] = {cols * 2, 128};
  cuuint32_t box[3] = {64, box_rows, 2}; cuuint32_t es[3] = {1, 1, 1};
  enc(m, CU_TENSOR_MAP_DATA_TYPE_BFLOAT16, 3, (void*)p, dims, st, box, es, CU_TENSOR_MAP_INTERLEAVE_NONE,
      CU_TENSOR_MAP_SWIZZLE_128B, CU_TENSOR_MAP_L2_PROMOTION_L2_256B, CU_TENSOR_MAP_FLOAT_OOB_FILL_NONE);
}

}

extern "C" void kernel_launch(void* const* d_in, const int* in_sizes, int n_in, void* d_out, int out_size) {
  (void)in_sizes; (void)n_in; (void)out_size;
  void* fn = nullptr; cudaDriverEntryPointQueryResult q;
  cudaGetDriverEntryPoint("cuTensorMapEncodeTiled", &fn, cudaEnableDefault, &q);
  PFN_enc enc = (PFN_enc)fn;
  void* oscr = nullptr; cudaGetSymbolAddress(&oscr, g_oscr);
  Params P;
  for (int i = 0; i < 2; i++) {
    enc2d(enc, &P.x[i], d_in[5*i + 0], 1024, TOK, 72);
    enc3d(enc, &P.k[i], d_in[5*i + 1], 128, 8 * 32 * 512, 128);
    enc3d(enc, &P.v[i], d_in[5*i + 2], 128, 8 * 32 * 512, 128);
    enc3d(enc, &P.wq[i], d_in[5*i + 3], 4096, 1024, 64);
    enc3d(enc, &P.wo[i], d_in[5*i + 4], 1024, 4096, 64);
    P.kptr[i] = (const char*)d_in[5*i + 1];
  }
  enc2d(enc, &P.os, oscr, 4096, 2 * TOK, 72);
  enc2d(enc, &P.oss, oscr, 4096, 2 * TOK, 24);
  enc2d(enc, &P.out, d_out, 2048, TOK, SQ);
  P.zero = 0;
  cudaFuncSetAttribute(fused_kernel, cudaFuncAttributeMaxDynamicSharedMemorySize, SMEM_BYTES);
  cudaLaunchConfig_t cfg = {};
  cfg.gridDim = dim3(NCTA); cfg.blockDim = dim3(384); cfg.dynamicSmemBytes = SMEM_BYTES; cfg.stream = cudaStreamPerThread;
  cudaLaunchAttribute at[1];
  at[0].id = cudaLaunchAttributeClusterDimension; at[0].val.clusterDim.x = 2; at[0].val.clusterDim.y = 1; at[0].val.clusterDim.z = 1;
  cfg.attrs = at; cfg.numAttrs = 1;
  cudaLaunchKernelEx(&cfg, fused_kernel, P);
}
```

```cpp
#include <cuda_runtime.h>
#include <cuda.h>
#include <cuda_bf16.h>
#include <stdint.h>

namespace {

constexpr int SQ = 144;
constexpr int TOK = 1152;
constexpr int SLOT = 18432;
constexpr int PAIR = 2 * SLOT;
constexpr int OFF_BAR = 6 * PAIR;
constexpr int OFF_MAX = OFF_BAR + 256;
constexpr int OFF_SUM = OFF_MAX + 2 * 576;
constexpr int OFF_INV = OFF_SUM + 8 * 288;
constexpr int SMEM_BYTES = OFF_INV + 576 + 1024;
constexpr int NCTA = 128;

struct alignas(64) Params {
  CUtensorMap x[2], wq[2], k[2], v[2], wo[2], os, oss, out;
  const char* kptr[2];
  uint32_t zero;
};

__device__ __nv_bfloat16 g_oscr[2 * TOK * 4096];
__device__ uint4 g_park[NCTA * 2 * (PAIR / 16)];
__device__ unsigned int g_cnt[64];
__device__ unsigned int g_done;

__device__ __forceinline__ uint32_t smem_u32(const void* p) { return (uint32_t)__cvta_generic_to_shared(p); }
__device__ __forceinline__ void mbar_init(uint32_t bar, int cnt) {
  asm volatile("mbarrier.init.shared::cta.b64 [%0], %1;" :: "r"(bar), "r"(cnt));
}
__device__ __forceinline__ void mbar_arrive(uint32_t bar, uint32_t cnt = 1) {
  asm volatile("mbarrier.arrive.shared::cta.b64 _, [%0], %1;" :: "r"(bar), "r"(cnt) : "memory");
}
__device__ __forceinline__ void mbar_wait(uint32_t bar, uint32_t parity) {
  asm volatile("{\n.reg .pred p;\n.reg .u32 c;\nmov.u32 c, 0;\n"
    "LAB_WAIT:\n"
    "mbarrier.try_wait.parity.shared::cta.b64 p, [%0], %1;\n"
    "@p bra DONE;\n"
    "add.u32 c, c, 1;\n"
    "setp.lt.u32 p, c, 400000;\n"
    "@p bra LAB_WAIT;\n"
    "DONE:\n}\n" :: "r"(bar), "r"(parity) : "memory");
}
#define ELECT_BEGIN "{\n.reg .pred p;\nelect.sync _|p, 0xffffffff;\n"
__device__ __forceinline__ void tma2d_mc(uint32_t dst, const CUtensorMap* map, int c0, int c1, uint32_t bar) {
  asm volatile(ELECT_BEGIN
    "@p cp.async.bulk.tensor.2d.shared::cluster.global.mbarrier::complete_tx::bytes.multicast::cluster [%0], [%1, {%3, %4}], [%2], %5;\n}\n"
    :: "r"(dst), "l"(map), "r"(bar), "r"(c0), "r"(c1), "h"((uint16_t)3) : "memory");
}
__device__ __forceinline__ void tma3d(uint32_t dst, const CUtensorMap* map, int c1, int c2, uint32_t bar, uint32_t bytes, uint64_t pol) {
  asm volatile(ELECT_BEGIN "@p mbarrier.arrive.expect_tx.shared::cta.b64 _, [%2], %6;\n"
    "@p cp.async.bulk.tensor.3d.shared::cluster.global.mbarrier::complete_tx::bytes.L2::cache_hint [%0], [%1, {%3, %4, %5}], [%2], %7;\n}\n"
    :: "r"(dst), "l"(map), "r"(bar), "r"(0), "r"(c1), "r"(c2), "r"(bytes), "l"(pol) : "memory");
}
__device__ __forceinline__ void bulk_load_pair(uint32_t dst, const void* src, uint32_t bar) {
  asm volatile(ELECT_BEGIN "@p mbarrier.arrive.expect_tx.shared::cta.b64 _, [%2], %3;\n"
    "@p cp.async.bulk.shared::cluster.global.mbarrier::complete_tx::bytes [%0], [%1], %3, [%2];\n}\n"
    :: "r"(dst), "l"(src), "r"(bar), "r"(PAIR) : "memory");
}
__device__ __forceinline__ void tma2d_store(const CUtensorMap* map, int c0, int c1, uint32_t src) {
  asm volatile("cp.async.bulk.tensor.2d.global.shared::cta.bulk_group [%0, {%1, %2}], [%3];"
    :: "l"(map), "r"(c0), "r"(c1), "r"(src) : "memory");
}
__device__ __forceinline__ uint64_t evict_first_policy() {
  uint64_t pol; asm volatile("createpolicy.fractional.L2::evict_first.b64 %0, 1.0;" : "=l"(pol)); return pol;
}
__device__ __forceinline__ void sched_sep(uint32_t zero) {
  asm volatile("{\n.reg .pred p;\n.reg .u32 c;\nSEP_L:\n.pragma \"nounroll\";\nmov.u32 c, %%clock;\nsetp.lt.u32 p, c, %0;\n@p bra SEP_L;\n}\n" :: "r"(zero) : "memory");
}
__device__ __forceinline__ void wg_fence() { asm volatile("wgmma.fence.sync.aligned;" ::: "memory"); }
__device__ __forceinline__ void wg_commit() { asm volatile("wgmma.commit_group.sync.aligned;" ::: "memory"); }
template<int N> __device__ __forceinline__ void wg_wait() { asm volatile("wgmma.wait_group.sync.aligned %0;" :: "n"(N) : "memory"); }
__device__ __forceinline__ void fence_regs(float (&d)[72]) {
  #pragma unroll
  for (int i = 0; i < 72; i++) asm volatile("" : "+f"(d[i]) :: "memory");
}
__device__ __forceinline__ void fence_async_smem() { asm volatile("fence.proxy.async.shared::cta;" ::: "memory"); }
template<int ID, int N> __device__ __forceinline__ void bar_sync() { asm volatile("bar.sync %0, %1;" :: "n"(ID), "n"(N) : "memory"); }
template<int ID, int N> __device__ __forceinline__ void bar_arrive() { asm volatile("bar.arrive %0, %1;" :: "n"(ID), "n"(N) : "memory"); }
__device__ __forceinline__ void cluster_sync() {
  asm volatile("barrier.cluster.arrive.relaxed.aligned;\nbarrier.cluster.wait.aligned;" ::: "memory");
}
__device__ __forceinline__ uint32_t pack_bf16(float lo, float hi) {
  uint32_t r; asm("cvt.rn.bf16x2.f32 %0, %1, %2;" : "=r"(r) : "f"(hi), "f"(lo)); return r;
}
__device__ __forceinline__ uint32_t max_bf16x2(uint32_t a, uint32_t b) {
  uint32_t r; asm("max.bf16x2 %0, %1, %2;" : "=r"(r) : "r"(a), "r"(b)); return r;
}
__device__ __forceinline__ uint32_t add_bf16x2(uint32_t a, uint32_t b) {
  uint32_t r; asm("add.rn.bf16x2 %0, %1, %2;" : "=r"(r) : "r"(a), "r"(b)); return r;
}
__device__ __forceinline__ uint32_t sub_bf16x2(uint32_t a, uint32_t b) {
  uint32_t r; asm("sub.rn.bf16x2 %0, %1, %2;" : "=r"(r) : "r"(a), "r"(b)); return r;
}
__device__ __forceinline__ uint32_t ex2_bf16x2(uint32_t a) {
  uint32_t r;
  asm("{\n.reg .b32 t;\nex2.approx.ftz.bf16x2 t, %1;\nmax.NaN.bf16x2 %0, t, %2;\n}\n" : "=r"(r) : "r"(a), "r"(0u));
  return r;
}
__device__ __forceinline__ void ex2_halves(uint32_t a, uint16_t& lo, uint16_t& hi) {
  asm volatile("{\n.reg .b16 l, h;\nmov.b32 {l, h}, %2;\nex2.approx.ftz.bf16 %0, l;\nex2.approx.ftz.bf16 %1, h;\n}\n" : "=h"(lo), "=h"(hi) : "r"(a));
}
__device__ __forceinline__ uint32_t pack_halves(uint16_t lo, uint16_t hi) {
  uint32_t r; asm volatile("mov.b32 %0, {%1, %2};" : "=r"(r) : "h"(lo), "h"(hi)); return r;
}
__device__ __forceinline__ uint32_t pack_halves_pin(uint16_t lo, uint16_t hi) {
  uint32_t r; asm volatile("{\n.reg .b32 t;\nmov.b32 t, {%1, %2};\nmax.NaN.bf16x2 %0, t, %3;\n}\n" : "=r"(r) : "h"(lo), "h"(hi), "r"(0u)); return r;
}
__device__ __forceinline__ float bf_lo(uint32_t v) { return __uint_as_float(v << 16); }
__device__ __forceinline__ float bf_hi(uint32_t v) { return __uint_as_float(v & 0xffff0000u); }
__device__ __forceinline__ void ldsm4t(uint32_t addr, uint32_t& a, uint32_t& b, uint32_t& c, uint32_t& d) {
  asm volatile("ldmatrix.sync.aligned.m8n8.x4.trans.shared.b16 {%0, %1, %2, %3}, [%4];"
    : "=r"(a), "=r"(b), "=r"(c), "=r"(d) : "r"(addr));
}
__device__ __forceinline__ void stsm4t(uint32_t addr, uint32_t a, uint32_t b, uint32_t c, uint32_t d) {
  asm volatile("stmatrix.sync.aligned.m8n8.x4.trans.shared.b16 [%0], {%1, %2, %3, %4};"
    :: "r"(addr), "r"(a), "r"(b), "r"(c), "r"(d));
}
__device__ __forceinline__ float4 lds128(uint32_t addr) {
  float4 v; asm volatile("ld.shared.v4.f32 {%0, %1, %2, %3}, [%4];" : "=f"(v.x), "=f"(v.y), "=f"(v.z), "=f"(v.w) : "r"(addr)); return v;
}
__device__ __forceinline__ void sts32(uint32_t addr, uint32_t v) { asm volatile("st.shared.u32 [%0], %1;" :: "r"(addr), "r"(v) : "memory"); }
__device__ __forceinline__ void red_max_f32(uint32_t addr, float v, bool on) {
  asm volatile("{\n.reg .pred p, q, e;\nsetp.ne.b32 e, %2, 0;\nsetp.ge.and.s32 p|q, %1, 0, e;\n"
               "@p red.shared.max.s32 [%0], %1;\n@q red.shared.min.u32 [%0], %1;\n}\n"
               :: "r"(addr), "r"(__float_as_uint(v)), "r"((uint32_t)on) : "memory");
}

#define ACC_REGS "{%0, %1, %2, %3, %4, %5, %6, %7, %8, %9, %10, %11, %12, %13, %14, %15, %16, %17, %18, %19, %20, %21, %22, %23, %24, %25, %26, %27, %28, %29, %30, %31, %32, %33, %34, %35, %36, %37, %38, %39, %40, %41, %42, %43, %44, %45, %46, %47, %48, %49, %50, %51, %52, %53, %54, %55, %56, %57, %58, %59, %60, %61, %62, %63, %64, %65, %66, %67, %68, %69, %70, %71}"
template<int TA, int OA, int OB>
__device__ __forceinline__ void mma(float (&d)[72], uint32_t a, uint32_t b) {
  asm volatile("{\n.reg .b64 da, db;\n.reg .b32 ta, tb, th;\n"
    "add.u32 ta, %72, %75;\nadd.u32 tb, %73, %76;\nmov.b32 th, 0x40000040;\n"
    "mov.b64 da, {ta, th};\nmov.b64 db, {tb, th};\n"
    "wgmma.mma_async.sync.aligned.m64n144k16.f32.bf16.bf16 " ACC_REGS ", da, db, 1, 1, 1, %74, 0;\n}\n"
    : "+f"(d[0]), "+f"(d[1]), "+f"(d[2]), "+f"(d[3]), "+f"(d[4]), "+f"(d[5]), "+f"(d[6]), "+f"(d[7]), "+f"(d[8]), "+f"(d[9]), "+f"(d[10]), "+f"(d[11]),
      "+f"(d[12]), "+f"(d[13]), "+f"(d[14]), "+f"(d[15]), "+f"(d[16]), "+f"(d[17]), "+f"(d[18]), "+f"(d[19]), "+f"(d[20]), "+f"(d[21]), "+f"(d[22]), "+f"(d[23]),
      "+f"(d[24]), "+f"(d[25]), "+f"(d[26]), "+f"(d[27]), "+f"(d[28]), "+f"(d[29]), "+f"(d[30]), "+f"(d[31]), "+f"(d[32]), "+f"(d[33]), "+f"(d[34]), "+f"(d[35]),
      "+f"(d[36]), "+f"(d[37]), "+f"(d[38]), "+f"(d[39]), "+f"(d[40]), "+f"(d[41]), "+f"(d[42]), "+f"(d[43]), "+f"(d[44]), "+f"(d[45]), "+f"(d[46]), "+f"(d[47]),
      "+f"(d[48]), "+f"(d[49]), "+f"(d[50]), "+f"(d[51]), "+f"(d[52]), "+f"(d[53]), "+f"(d[54]), "+f"(d[55]), "+f"(d[56]), "+f"(d[57]), "+f"(d[58]), "+f"(d[59]),
      "+f"(d[60]), "+f"(d[61]), "+f"(d[62]), "+f"(d[63]), "+f"(d[64]), "+f"(d[65]), "+f"(d[66]), "+f"(d[67]), "+f"(d[68]), "+f"(d[69]), "+f"(d[70]), "+f"(d[71])
    : "r"(a), "r"(b), "n"(TA), "n"(OA / 16), "n"(OB / 16));
}
template<int TA, int OA, int OB>
__device__ __forceinline__ void mma_init(float (&d)[72], uint32_t a, uint32_t b) {
  asm volatile("{\n.reg .b64 da, db;\n.reg .b32 ta, tb, th;\n"
    "add.u32 ta, %72, %75;\nadd.u32 tb, %73, %76;\nmov.b32 th, 0x40000040;\n"
    "mov.b64 da, {ta, th};\nmov.b64 db, {tb, th};\n"
    "wgmma.mma_async.sync.aligned.m64n144k16.f32.bf16.bf16 " ACC_REGS ", da, db, 0, 1, 1, %74, 0;\n}\n"
    : "=f"(d[0]), "=f"(d[1]), "=f"(d[2]), "=f"(d[3]), "=f"(d[4]), "=f"(d[5]), "=f"(d[6]), "=f"(d[7]), "=f"(d[8]), "=f"(d[9]), "=f"(d[10]), "=f"(d[11]),
      "=f"(d[12]), "=f"(d[13]), "=f"(d[14]), "=f"(d[15]), "=f"(d[16]), "=f"(d[17]), "=f"(d[18]), "=f"(d[19]), "=f"(d[20]), "=f"(d[21]), "=f"(d[22]), "=f"(d[23]),
      "=f"(d[24]), "=f"(d[25]), "=f"(d[26]), "=f"(d[27]), "=f"(d[28]), "=f"(d[29]), "=f"(d[30]), "=f"(d[31]), "=f"(d[32]), "=f"(d[33]), "=f"(d[34]), "=f"(d[35]),
      "=f"(d[36]), "=f"(d[37]), "=f"(d[38]), "=f"(d[39]), "=f"(d[40]), "=f"(d[41]), "=f"(d[42]), "=f"(d[43]), "=f"(d[44]), "=f"(d[45]), "=f"(d[46]), "=f"(d[47]),
      "=f"(d[48]), "=f"(d[49]), "=f"(d[50]), "=f"(d[51]), "=f"(d[52]), "=f"(d[53]), "=f"(d[54]), "=f"(d[55]), "=f"(d[56]), "=f"(d[57]), "=f"(d[58]), "=f"(d[59]),
      "=f"(d[60]), "=f"(d[61]), "=f"(d[62]), "=f"(d[63]), "=f"(d[64]), "=f"(d[65]), "=f"(d[66]), "=f"(d[67]), "=f"(d[68]), "=f"(d[69]), "=f"(d[70]), "=f"(d[71])
    : "r"(a), "r"(b), "n"(TA), "n"(OA / 16), "n"(OB / 16));
}
template<int OB>
__device__ __forceinline__ void mma_rs(float (&d)[72], uint32_t diag, uint32_t b) {
  asm volatile("{\n.reg .b64 db;\n.reg .b32 tb, th, z;\n"
    "add.u32 tb, %73, %74;\nmov.b32 th, 0x40000040;\nmov.b32 z, 0;\nmov.b64 db, {tb, th};\n"
    "wgmma.mma_async.sync.aligned.m64n144k16.f32.bf16.bf16 " ACC_REGS ", {%72, z, z, %72}, db, 1, 1, 1, 0;\n}\n"
    : "+f"(d[0]), "+f"(d[1]), "+f"(d[2]), "+f"(d[3]), "+f"(d[4]), "+f"(d[5]), "+f"(d[6]), "+f"(d[7]), "+f"(d[8]), "+f"(d[9]), "+f"(d[10]), "+f"(d[11]),
      "+f"(d[12]), "+f"(d[13]), "+f"(d[14]), "+f"(d[15]), "+f"(d[16]), "+f"(d[17]), "+f"(d[18]), "+f"(d[19]), "+f"(d[20]), "+f"(d[21]), "+f"(d[22]), "+f"(d[23]),
      "+f"(d[24]), "+f"(d[25]), "+f"(d[26]), "+f"(d[27]), "+f"(d[28]), "+f"(d[29]), "+f"(d[30]), "+f"(d[31]), "+f"(d[32]), "+f"(d[33]), "+f"(d[34]), "+f"(d[35]),
      "+f"(d[36]), "+f"(d[37]), "+f"(d[38]), "+f"(d[39]), "+f"(d[40]), "+f"(d[41]), "+f"(d[42]), "+f"(d[43]), "+f"(d[44]), "+f"(d[45]), "+f"(d[46]), "+f"(d[47]),
      "+f"(d[48]), "+f"(d[49]), "+f"(d[50]), "+f"(d[51]), "+f"(d[52]), "+f"(d[53]), "+f"(d[54]), "+f"(d[55]), "+f"(d[56]), "+f"(d[57]), "+f"(d[58]), "+f"(d[59]),
      "+f"(d[60]), "+f"(d[61]), "+f"(d[62]), "+f"(d[63]), "+f"(d[64]), "+f"(d[65]), "+f"(d[66]), "+f"(d[67]), "+f"(d[68]), "+f"(d[69]), "+f"(d[70]), "+f"(d[71])
    : "r"(diag), "r"(b), "n"(OB / 16));
}

__device__ __forceinline__ void store_acc_T(const float (&d)[72], uint32_t addr) {
  #pragma unroll
  for (int j = 0; j < 18; j += 2)
    stsm4t(addr + j * 1024, pack_bf16(d[4*j], d[4*j+1]), pack_bf16(d[4*j+2], d[4*j+3]),
           pack_bf16(d[4*j+4], d[4*j+5]), pack_bf16(d[4*j+6], d[4*j+7]));
}

template<bool IS_MAX>
__device__ __forceinline__ void warp_col_reduce(const uint32_t (&v)[18], uint32_t (&r3)[3], int lane) {
  #define OP(a, b) (IS_MAX ? max_bf16x2(a, b) : add_bf16x2(a, b))
  const bool b4 = lane & 16, b3 = lane & 8, b2 = lane & 4;
  uint32_t r1[9], r2[5];
  #pragma unroll
  for (int k = 0; k < 9; k++) {
    const uint32_t snd = b4 ? v[k] : v[k+9], kp = b4 ? v[k+9] : v[k];
    r1[k] = OP(kp, __shfl_xor_sync(0xffffffff, snd, 16));
  }
  #pragma unroll
  for (int k = 0; k < 4; k++) {
    const uint32_t snd = b3 ? r1[k] : r1[k+4], kp = b3 ? r1[k+4] : r1[k];
    r2[k] = OP(kp, __shfl_xor_sync(0xffffffff, snd, 8));
  }
  r2[4] = OP(r1[8], __shfl_xor_sync(0xffffffff, r1[8], 8));
  #pragma unroll
  for (int k = 0; k < 2; k++) {
    const uint32_t snd = b2 ? r2[k] : r2[k+2], kp = b2 ? r2[k+2] : r2[k];
    r3[k] = OP(kp, __shfl_xor_sync(0xffffffff, snd, 4));
  }
  r3[2] = OP(r2[4], __shfl_xor_sync(0xffffffff, r2[4], 4));
  #undef OP
}

constexpr uint32_t XLAP = 0x12435u, GLAP0 = 0x53241u, GLAP = 0x54321u;
struct Seg { int isq, head_or_k0, n, np; uint32_t lap, lap2; int lap0; };
__device__ __forceinline__ Seg seg_info(int n, int sh) {
  Seg s;
  s.isq = n <= 4 - sh;
  s.head_or_k0 = n == 0 ? 3 : (s.isq ? n - 1 : (n - 5 + sh) * 16);
  s.np = n == 6 ? 1 + sh : 0;
  s.n = n == 6 ? 49 - 15 * sh : 16;
  const bool g = n >= 2 && n <= 5;
  s.lap = g ? GLAP0 : XLAP;
  s.lap2 = g ? GLAP : XLAP;
  s.lap0 = n == 0 ? 4 : 0;
  return s;
}

__global__ void __launch_bounds__(384, 1) fused_kernel(const __grid_constant__ Params P) {
  extern __shared__ __align__(1024) char smem_raw[];
  const uint32_t sb = (smem_u32(smem_raw) + 1023u) & ~1023u;
  const uint32_t full0 = sb + OFF_BAR;
  const uint32_t emptyB = full0 + 48;
  const uint32_t emptyA = full0 + 192;
  const uint32_t stg0 = full0 + 96, maxbar = full0 + 104, stgfree = full0 + 112, ordy = full0 + 144;
  const uint32_t kvcnt = full0 + 128;
  const int tid = threadIdx.x;
  const int wg = __shfl_sync(0xffffffff, tid >> 7, 0);
  uint32_t rank; asm volatile("mov.u32 %0, %%cluster_ctarank;" : "=r"(rank));
  int cl;
  {
    const int c = blockIdx.x >> 1, t = c - 4;
    int set, idx;
    if (c < 4) { set = 1; idx = c; }
    else if (t < 32) { set = 2 * (t & 7); idx = t >> 3; }
    else { set = 2 * (1 + (t - 32) % 7) + 1; idx = (t - 32) / 7; }
    cl = set * 4 + idx;
    cl = (cl & 7) | (((cl >> 3) & 1) << 5) | ((cl >> 4) << 3);
  }
  const int blk = cl >> 5, b = cl & 7, sub = ((cl >> 3) & 3) * 2 + rank, sh = blk;
  uint4* const park = g_park + (cl * 2 + rank) * (2 * (PAIR / 16));

  if (tid == 0) {
    for (int i = 0; i < 6; i++) { mbar_init(full0 + 8*i, 1); mbar_init(emptyB + 8*i, 4); mbar_init(emptyA + 8*i, 2); }
    mbar_init(stg0, 8); mbar_init(maxbar, 8); mbar_init(stgfree, 1);
    for (int i = 0; i < 4; i++) mbar_init(ordy + 8*i, 1);
    asm volatile("fence.mbarrier_init.release.cluster;" ::: "memory");
  }
  if (tid < 288) sts32(sb + OFF_MAX + tid * 4, 0xff800000u);
  if (tid == 300) sts32(kvcnt, 0u);
  __syncthreads();
  cluster_sync();

  if (wg == 2) {
    asm volatile("setmaxnreg.dec.sync.aligned.u32 24;");
    const int warp = __shfl_sync(0xffffffff, (tid >> 5) & 3, 0);
    const int lane = tid & 31;
    const uint32_t ebar = warp == 0 ? emptyA : emptyB;
    #define ACQ(s) do { mbar_wait(ebar + 8*(s), (eph >> (s)) & 1); eph ^= 1u << (s); } while (0)
    if (warp == 0) {
      uint32_t eph = 0x3Fu;
      const uint64_t pol = evict_first_policy();
      int nkv = 0;
      uint32_t tlast = (uint32_t)clock64();
      #pragma unroll 1
      for (int n = 1 - sh; n < 7; n++) {
        Seg sg = seg_info(n, sh);
        const CUtensorMap* map = sg.isq ? &P.wq[blk] : &P.wo[blk];
        const int k0 = sg.isq ? 0 : sg.head_or_k0, col = (sg.isq ? sg.head_or_k0 * 8 + sub : sub) * 2;
        int lp = sg.lap0;
        #pragma unroll 1
        for (int j = 0; j < sg.n; j++) {
          const int s = (sg.lap >> (lp * 4)) & 15;
          const int kk = k0 + j - sg.np;
          if (j < sg.np) {
            if (j == 1) { mbar_wait(ordy + 16, 0); ACQ(s); bulk_load_pair(sb + s * PAIR, park, full0 + 8*s); }
          } else {
            ACQ(s);
            tma3d(sb + s * PAIR + SLOT, map, kk * 64, col, full0 + 8*s, 18432 + 16384, pol);
          }
          if (++lp == 5) { lp = 0; sg.lap = sg.lap2; }
        }
        #pragma unroll 1
        for (int q = (n >= 2 && n <= 5 ? 0 : 4); q < (n >= 1 && n <= 4 ? 8 : 4); q++) {
          if (sh && n == 4 && q == 4) { mbar_wait(ordy, 0); ACQ(5); bulk_load_pair(sb + 5 * PAIR, park + PAIR / 16, full0 + 40); }
          const int s = (0x32432432u >> (q * 4)) & 15;
          const int head = (q < 4 ? n - 2 : n - 1) * 8 + sub;
          ACQ(s);
          { const int gap = (q == 1 || q == 2) ? 1300 : 0;
            while ((int)((uint32_t)clock64() - tlast) < gap) __nanosleep(30);
            tlast = (uint32_t)clock64(); }
          tma3d(sb + s * PAIR, q < 4 ? &P.v[blk] : &P.k[blk], (b * 32 + head) * 512 + ((q < 4 ? q : q + 1) & 3) * 128, 0, full0 + 8*s, 32768, pol);
          nkv++;
          asm volatile("st.volatile.shared.u32 [%0], %1;" :: "r"(kvcnt), "r"(nkv) : "memory");
        }
      }
    } else if (warp == 1) {
      uint32_t eph = 0x3Fu;
      #pragma unroll 1
      for (int n = 1 - sh; n < 7; n++) {
        Seg sg = seg_info(n, sh);
        const CUtensorMap* map = sg.isq ? &P.x[blk] : &P.os;
        const int row = (sg.isq ? 0 : blk * TOK) + b * SQ + rank * 72, k0 = sg.isq ? 0 : sg.head_or_k0;
        int lp = sg.lap0;
        #pragma unroll 1
        for (int j = 0; j < sg.n; j++) {
          const int s = (sg.lap >> (lp * 4)) & 15;
          if (j >= sg.np) {
            const int kk = k0 + j - sg.np;
            if (!sg.isq && (kk & 15) == 0) mbar_wait(ordy + 8 * (kk >> 4), 0);
            ACQ(s);
            tma2d_mc(sb + s * PAIR + rank * 9216, map, kk * 64, row, full0 + 8*s);
          }
          if (++lp == 5) { lp = 0; sg.lap = sg.lap2; }
        }
      }
    } else if (warp == 2) {
      uint32_t ph = 0;
      #define PARK_STORE(slot, pair) do { if (lane == 0) { mbar_wait(stg0, ph); \
          _Pragma("unroll 1") for (int pc = 0; pc < 12; pc++) \
            asm volatile("cp.async.bulk.global.shared::cta.bulk_group [%0], [%1], %2;" :: "l"(park + (slot) * (PAIR / 16) + pc * 192), "r"(sb + (pair) * PAIR + pc * 3072), "r"(3072) : "memory"); \
          asm volatile("cp.async.bulk.commit_group;" ::: "memory"); \
          asm volatile("cp.async.bulk.wait_group.read 0;" ::: "memory"); \
          if (pair) mbar_arrive(emptyA + 40, 2); else mbar_arrive(stgfree); } \
          ph ^= 1; __syncwarp(); } while (0)
      if (sh) PARK_STORE(1, 0);
      #pragma unroll 1
      for (int n = 0; n < 4; n++) {
        if (n == 2 && sh) PARK_STORE(0, 5);
        bar_sync<4, 288>();
        #pragma unroll
        for (int r = 0; r < 3; r++) {
          const int idx = r * 32 + lane;
          if (idx < 72) {
            float s0 = 0.f, s1 = 0.f;
            #pragma unroll
            for (int ww = 0; ww < 8; ww++) {
              uint32_t v; asm volatile("ld.shared.u32 %0, [%1];" : "=r"(v) : "r"(sb + OFF_SUM + ww * 288 + idx * 4));
              s0 += bf_lo(v); s1 += bf_hi(v);
            }
            asm volatile("st.shared.v2.f32 [%0], {%1, %2};" :: "r"(sb + OFF_INV + idx * 8), "f"(__fdividef(1.f, s0)), "f"(__fdividef(1.f, s1)) : "memory");
          }
        }
        bar_arrive<7, 160>();
        bar_arrive<8, 160>();
        if (lane == 0) {
          mbar_wait(stg0, ph);
          #pragma unroll 1
          for (int pc = 0; pc < 12; pc++)
            tma2d_store(&P.oss, (n * 8 + sub) * 128 + (pc & 1) * 64, blk * TOK + b * SQ + (pc >> 1) * 24, sb + (pc & 1) * SLOT + (pc >> 1) * 3072);
          asm volatile("cp.async.bulk.commit_group;" ::: "memory");
          asm volatile("cp.async.bulk.wait_group.read 0;" ::: "memory");
          mbar_arrive(stgfree);
          asm volatile("cp.async.bulk.wait_group 0;" ::: "memory");
          asm volatile("fence.proxy.async.global;" ::: "memory");
          asm volatile("red.release.gpu.global.add.u32 [%0], %1;" :: "l"(&g_cnt[(blk * 8 + b) * 4 + n]), "r"(1u) : "memory");
        }
        ph ^= 1;
        __syncwarp();
      }
      if (lane == 0) {
        mbar_wait(stg0, ph);
        tma2d_store(&P.out, blk * 1024 + sub * 128, b * SQ, sb);
        tma2d_store(&P.out, blk * 1024 + sub * 128 + 64, b * SQ, sb + SLOT);
        asm volatile("cp.async.bulk.commit_group;" ::: "memory");
        asm volatile("cp.async.bulk.wait_group.read 0;" ::: "memory");
      }
    } else {
      unsigned int epoch;
      asm volatile("ld.relaxed.gpu.global.u32 %0, [%1];" : "=r"(epoch) : "l"(&g_done) : "memory");
      const unsigned int target = 8u * ((epoch >> 7) + 1);
      {
        const char* kp = P.kptr[blk] + (size_t)(b * 32 + sub) * (512 * 256) + lane * 256;
        uint32_t v0 = 0, v1 = 0;
        uint32_t tnext = (uint32_t)clock64() + (sh ? 11000 : 2000);
        int q = 0;
        #pragma unroll 1
        for (int spin = 0; spin < 1000000 && q < 8; spin++) {
          int cnt; asm volatile("ld.volatile.shared.u32 %0, [%1];" : "=r"(cnt) : "r"(kvcnt) : "memory");
          if (q < cnt * 2) q = cnt * 2;
          const uint32_t now = (uint32_t)clock64();
          if ((int)(now - tnext) >= 0 && q < 8) {
            const char* a = kp + ((q + 2) & 7) * 16384;
            asm volatile("st.volatile.shared.u32 [%0], %1;" :: "r"(kvcnt + 8), "r"(v0 ^ v1) : "memory");
            asm volatile("ld.global.L2::256B.u32 %0, [%1];" : "=r"(v0) : "l"(a) : "memory");
            asm volatile("ld.global.L2::256B.u32 %0, [%1];" : "=r"(v1) : "l"(a + 8192) : "memory");
            q++; tnext = now + (sh ? 1400 : 900);
          } else __nanosleep(50);
        }
        asm volatile("st.volatile.shared.u32 [%0], %1;" :: "r"(kvcnt + 8), "r"(v0 ^ v1) : "memory");
      }
      int nrdy = 0;
      #pragma unroll 1
      for (int spin = 0; spin < 1000000 && nrdy < 4; spin++) {
        int cnt; asm volatile("ld.volatile.shared.u32 %0, [%1];" : "=r"(cnt) : "r"(kvcnt) : "memory");
        if (cnt >= nrdy * 8 + 8) {
          unsigned int c; asm volatile("ld.acquire.gpu.global.u32 %0, [%1];" : "=r"(c) : "l"(&g_cnt[(blk * 8 + b) * 4 + nrdy]) : "memory");
          if ((int)(c - target) >= 0) {
            asm volatile("fence.proxy.async.global;" ::: "memory");
            __syncwarp();
            if (lane == 0) mbar_arrive(ordy + 8 * nrdy);
            nrdy++;
          }
        }
        __nanosleep(100);
      }
      if (lane == 0) atomicAdd(&g_done, 1u);
    }
    __syncwarp();
    cluster_sync();
  } else {
    asm volatile("setmaxnreg.inc.sync.aligned.u32 240;");
    const int w = wg;
    int t128 = tid & 127;
    asm volatile("" : "+r"(t128));
    #define lane (t128 & 31)
    #define warp (t128 >> 5)
    const uint32_t st_base = sb + w * SLOT + (uint32_t)(((lane >> 4) * 8 + (lane & 7)) * 128 + (((2 * warp + ((lane >> 3) & 1)) ^ (lane & 7)) << 4));
    const uint32_t d0 = ((sb & 0x3FFFF) >> 4) | (64u << 16);
    const uint32_t d0w = d0 + w * 512, d0v = d0 + w * 1024;
    uint32_t rel_addr; asm("mapa.shared::cluster.u32 %0, %1, %2;" : "=r"(rel_addr) : "r"(t128 == 0 ? emptyA : emptyB), "r"(t128 == 0 ? rank : (uint32_t)(t128 & 1)));
    #define WAITF(s, flip) mbar_wait(full0 + 8*(s), ((fph >> (s)) & 1) ^ (flip))
    #define RELX(s, all) asm volatile("{\n.reg .pred p;\nsetp.lt.u32 p, %1, %2;\n@p mbarrier.arrive.relaxed.cluster.shared::cluster.b64 _, [%0];\n}\n" :: "r"(rel_addr + 8*(s)), "r"(t128), "r"((all) ? 3 : 1) : "memory")
    #define REL(s) RELX(s, true)
    #define STG_ARRIVE() do { fence_async_smem(); __syncwarp(); if (lane == 0) mbar_arrive(stg0); } while (0)
    #define STG_FREE() do { mbar_wait(stgfree, sfp); sfp ^= 1; } while (0)
    #define TURN_WAIT() do { if (w) bar_sync<6, 256>(); else bar_sync<5, 256>(); } while (0)
    #define TURN_PASS() do { if (w) bar_arrive<5, 256>(); else bar_arrive<6, 256>(); } while (0)
    #define GMMA(acc, da, db, O, first) do { if (!(first)) fence_regs(acc); wg_fence(); \
        if (first) mma_init<1, (O) + SLOT, (O)>(acc, da, db); else mma<1, (O) + SLOT, (O)>(acc, da, db); \
        mma<1, (O) + SLOT + 2048, (O) + 32>(acc, da, db); mma<1, (O) + SLOT + 4096, (O) + 64>(acc, da, db); \
        mma<1, (O) + SLOT + 6144, (O) + 96>(acc, da, db); wg_commit(); } while (0)
    const float cs = 0.08838834764831845f * 1.4426950408889634f;
    uint32_t fph = 0, sfp = 0;
    #define XLOOP(a0, j0, n, lp0, tail_local) do { int lp = lp0; \
        _Pragma("unroll 1") for (int j = j0; j < n; j++) { \
          const int s_ = (XLAP >> (lp * 4)) & 15; \
          WAITF(s_, 0); fph ^= 1u << s_; \
          const uint32_t off = s_ * (PAIR / 16); \
          GMMA(a0, d0w + off, d0 + off, 0, false); \
          wg_wait<1>(); \
          if (j > j0) RELX(sprev, !((tail_local) && j > n - 5 && sprev >= 2 && sprev <= 4)); \
          sprev = s_; \
          if (++lp == 5) lp = 0; \
        } } while (0)
    #pragma unroll 1
    for (int h = -sh; h <= 0; h++) {
      float a0[72];
      #pragma unroll
      for (int i = 0; i < 72; i++) a0[i] = 0.f;
      int sprev = 0;
      XLOOP(a0, 0, 16, h ? 4 : 0, h == 0);
      wg_wait<0>();
      fence_regs(a0);
      if (h == 0) bar_sync<3, 256>(); else REL(sprev);
      #pragma unroll
      for (int i = 0; i < 72; i++) a0[i] *= cs;
      store_acc_T(a0, st_base + (h == 0 ? 5 * PAIR : 0));
      fence_async_smem();
      if (h != 0) { __syncwarp(); if (lane == 0) mbar_arrive(stg0); }
    }
    if (w) bar_arrive<5, 256>();
    uint32_t sp[3][36];
    uint32_t mx[18];
        #define PACK(s, i) do { _Pragma("unroll") for (int j = 0; j < 18; j++) { \
            sp[i][2*j] = pack_bf16(s[4*j], s[4*j+1]); sp[i][2*j+1] = pack_bf16(s[4*j+2], s[4*j+3]); \
            const uint32_t m2 = max_bf16x2(sp[i][2*j], sp[i][2*j+1]); \
            mx[j] = (i) ? max_bf16x2(mx[j], m2) : m2; \
            asm volatile("" : "+r"(sp[i][2*j]), "+r"(sp[i][2*j+1]), "+r"(mx[j]) :: "memory"); } } while (0)
        #define SISSUE(s, p, fin) do { TURN_WAIT(); wg_fence(); \
            mma_init<0, (p) * PAIR, 5 * PAIR>(s, d0w, d0);      mma<0, (p) * PAIR + 32, 5 * PAIR + 32>(s, d0w, d0); \
            mma<0, (p) * PAIR + 64, 5 * PAIR + 64>(s, d0w, d0); mma<0, (p) * PAIR + 96, 5 * PAIR + 96>(s, d0w, d0); \
            mma<0, (p) * PAIR + 16384, 5 * PAIR + SLOT>(s, d0w, d0);           mma<0, (p) * PAIR + 16384 + 32, 5 * PAIR + SLOT + 32>(s, d0w, d0); \
            mma<0, (p) * PAIR + 16384 + 64, 5 * PAIR + SLOT + 64>(s, d0w, d0); mma<0, (p) * PAIR + 16384 + 96, 5 * PAIR + SLOT + 96>(s, d0w, d0); \
            wg_commit(); if (!(fin) || !w) TURN_PASS(); } while (0)
    #define O_NORM_STSM() do { _Pragma("unroll") for (int c_ = 0; c_ < 9; c_++) \
        stsm4t(st_base + c_ * 2048, pack_bf16(o[8*c_] * iv[c_].x, o[8*c_+1] * iv[c_].y), pack_bf16(o[8*c_+2] * iv[c_].x, o[8*c_+3] * iv[c_].y), \
               pack_bf16(o[8*c_+4] * iv[c_].z, o[8*c_+5] * iv[c_].w), pack_bf16(o[8*c_+6] * iv[c_].z, o[8*c_+7] * iv[c_].w)); } while (0)
    #define PHASE_S(with_o, wait_stg) do { \
        float sa[72], sc[72], s[72]; \
        WAITF(3, 0); \
        SISSUE(sa, 3, false); \
        with_o; \
        wg_wait<0>(); fence_regs(sa); RELX(3, false); \
        WAITF(4, 0); \
        SISSUE(sc, 4, false); \
        sched_sep(P.zero); \
        PACK(sa, 0); \
        if (sizeof(#with_o) > 1) STG_ARRIVE(); \
        sched_sep(P.zero); \
        wg_wait<0>(); fence_regs(sc); REL(4); \
        PACK(sc, 1); \
        WAITF(2, 0); \
        SISSUE(sc, 2, false); \
        wg_wait<0>(); fence_regs(sc); REL(2); \
        PACK(sc, 2); \
        WAITF(3, 1); \
        SISSUE(s, 3, true); \
        wg_wait<0>(); fence_regs(s); REL(3); REL(5); \
        if (wait_stg) STG_FREE(); \
        _Pragma("unroll") for (int c = 0; c < 9; c++) { \
          const uint32_t k0 = pack_bf16(s[8*c], s[8*c+1]), k1 = pack_bf16(s[8*c+2], s[8*c+3]); \
          const uint32_t k2 = pack_bf16(s[8*c+4], s[8*c+5]), k3 = pack_bf16(s[8*c+6], s[8*c+7]); \
          stsm4t(st_base + c * 2048, k0, k1, k2, k3); \
          mx[2*c] = max_bf16x2(mx[2*c], max_bf16x2(k0, k1)); \
          mx[2*c+1] = max_bf16x2(mx[2*c+1], max_bf16x2(k2, k3)); \
          asm volatile("" : "+r"(mx[2*c]), "+r"(mx[2*c+1]) :: "memory"); \
        } \
        fph ^= 0x14u; } while (0)
    PHASE_S(, sh);
    #pragma unroll 1
    for (int h = 0; ; h++) {
      const uint32_t hodd = h & 1;
      const bool last = h == 3, gq = h + sh < 3;
      const uint32_t ma = sb + OFF_MAX + hodd * 576 + (lane & 3) * 144;
      uint32_t l2[18];
      {
        float a0[72];
        #define U0(j) ((j) <= 2 ? 0 : ((j) >= 16 ? 27 : (((j) - 2) * 27) / 14))
        uint32_t mm[2][2], pk[2][4];
        float4 mr;
        uint16_t eh[2][8];
        #define GP(j) ((j) < 0 ? 1 : ((j) < 5 ? (int)((GLAP0 >> (((j) & 7) * 4)) & 15) : 1 + (j) % 5))
        #define GSTEP(j) do { \
          WAITF(GP(j), ((j) / 5) & 1); \
          if ((j) > 0) { wg_wait<0>(); if ((j) < 15) RELX(GP((j) - 1), (j) < 12); } \
          if ((j) == 1) mbar_wait(maxbar, hodd); \
          GMEM(j); \
          GMMA(a0, d0w, d0, GP(j) * PAIR, (j) == 0); \
          if ((j) == 0) { \
            uint32_t r3[3]; warp_col_reduce<true>(mx, r3, lane); \
            const int jb = (lane & 16) ? 9 : 0, j0 = jb + ((lane & 8) ? 4 : 0) + ((lane & 4) ? 2 : 0); \
            red_max_f32(ma + j0 * 8, bf_lo(r3[0]), true);      red_max_f32(ma + j0 * 8 + 4, bf_hi(r3[0]), true); \
            red_max_f32(ma + j0 * 8 + 8, bf_lo(r3[1]), true);  red_max_f32(ma + j0 * 8 + 12, bf_hi(r3[1]), true); \
            red_max_f32(ma + (jb + 8) * 8, bf_lo(r3[2]), !(lane & 12)); red_max_f32(ma + (jb + 8) * 8 + 4, bf_hi(r3[2]), !(lane & 12)); \
            __syncwarp(); if (lane == 0) mbar_arrive(maxbar); } \
          GEXP(j); } while (0)
        #define GMEM(j) do { \
          _Pragma("unroll") for (int u = U0(j); u < U0((j) + 1); u++) if (u % 3 == 0) { \
            mm[(u / 3) & 1][0] = __byte_perm(__float_as_uint(mr.x), __float_as_uint(mr.y), 0x7632); \
            mm[(u / 3) & 1][1] = __byte_perm(__float_as_uint(mr.z), __float_as_uint(mr.w), 0x7632); } \
          _Pragma("unroll") for (int u = U0((j) - 1); u < U0(j); u++) if (u % 3 == 0) { \
            const int c = u / 3; uint16_t (&e)[8] = eh[u - U0((j) - 1)]; \
            const uint32_t k0 = pack_halves(e[0], e[1]), k1 = pack_halves(e[2], e[3]), k2 = pack_halves(e[4], e[5]), k3 = pack_halves(e[6], e[7]); \
            stsm4t(st_base + c * 2048, k0, k1, k2, k3); \
            l2[2*c] = add_bf16x2(k0, k1); l2[2*c+1] = add_bf16x2(k2, k3); asm volatile("" : "+r"(l2[2*c]), "+r"(l2[2*c+1])); } \
          _Pragma("unroll") for (int u = U0((j) + 1); u < U0((j) + 2); u++) if (u % 3 == 0) { \
            const int c = u / 3; \
            mr = lds128(ma + c * 16); \
            ldsm4t(st_base + c * 2048, pk[c & 1][0], pk[c & 1][1], pk[c & 1][2], pk[c & 1][3]); \
          } } while (0)
        #define GEXP(j) do { \
          _Pragma("unroll") for (int u = U0((j) - 1); u < U0(j); u++) if (u % 3) { \
            const int c = u / 3, t = u % 3; uint16_t (&e)[8] = eh[u - U0((j) - 1)]; \
            uint32_t (&q)[36] = sp[t ? t - 1 : 0]; \
            q[4*c] = pack_halves_pin(e[0], e[1]); q[4*c+1] = pack_halves_pin(e[2], e[3]); \
            q[4*c+2] = pack_halves_pin(e[4], e[5]); q[4*c+3] = pack_halves_pin(e[6], e[7]); \
            l2[2*c] = add_bf16x2(l2[2*c], add_bf16x2(q[4*c], q[4*c+1])); l2[2*c+1] = add_bf16x2(l2[2*c+1], add_bf16x2(q[4*c+2], q[4*c+3])); \
            asm volatile("" : "+r"(l2[2*c]), "+r"(l2[2*c+1])); \
          } \
          _Pragma("unroll") for (int u = U0(j); u < U0((j) + 1); u++) { \
            const int c = u / 3, t = u % 3; uint16_t (&e)[8] = eh[u - U0(j)]; \
            const uint32_t* q = t ? &sp[t ? t - 1 : 0][4*c] : pk[c & 1]; \
            ex2_halves(sub_bf16x2(q[0], mm[c & 1][0]), e[0], e[1]); ex2_halves(sub_bf16x2(q[1], mm[c & 1][0]), e[2], e[3]); \
            ex2_halves(sub_bf16x2(q[2], mm[c & 1][1]), e[4], e[5]); ex2_halves(sub_bf16x2(q[3], mm[c & 1][1]), e[6], e[7]); \
            if (t == 1) { \
              sp[2][4*c] = sub_bf16x2(sp[2][4*c], mm[c & 1][0]); sp[2][4*c+1] = sub_bf16x2(sp[2][4*c+1], mm[c & 1][0]); \
              sp[2][4*c+2] = sub_bf16x2(sp[2][4*c+2], mm[c & 1][1]); sp[2][4*c+3] = sub_bf16x2(sp[2][4*c+3], mm[c & 1][1]); \
              asm volatile("" : "+r"(sp[2][4*c]), "+r"(sp[2][4*c+1]), "+r"(sp[2][4*c+2]), "+r"(sp[2][4*c+3])); } \
          } } while (0)
        GSTEP(0); GSTEP(1); GSTEP(2); GSTEP(3); GSTEP(4); GSTEP(5); GSTEP(6); GSTEP(7);
        GSTEP(8); GSTEP(9); GSTEP(10); GSTEP(11); GSTEP(12); GSTEP(13); GSTEP(14); GSTEP(15);
        fph ^= 0x3Cu;
        WAITF(2, 0);
        GMEM(16); GEXP(16);
        fence_async_smem();
        bar_sync<3, 256>();
        wg_wait<0>();
        fence_regs(a0);
        if (w) bar_arrive<10, 256>();
        if (gq) {
          #pragma unroll
          for (int i = 0; i < 72; i++) a0[i] *= cs;
        }
        store_acc_T(a0, st_base + 5 * PAIR);
        if (!gq && !last) STG_ARRIVE();
      }
      float o[72];
      #define STORE_P(i) do { _Pragma("unroll") for (int c_ = 0; c_ < 9; c_++) \
          stsm4t(st_base + ((i) & 1) * PAIR + c_ * 2048, sp[(i)-1][4*c_], sp[(i)-1][4*c_+1], sp[(i)-1][4*c_+2], sp[(i)-1][4*c_+3]); } while (0)
      #define PVSTEP(i) do { \
        constexpr int v_ = (i) == 3 ? 2 : 2 + (i), pb_ = ((i) & 1) * PAIR; \
        if ((i) > 0) { \
          if (!w) { bar_sync<9 + ((i) & 1), 256>(); STORE_P((i) ? (i) : 1); } \
          if ((i) == 3) { \
            uint32_t r3[3]; \
            warp_col_reduce<false>(l2, r3, lane); \
            const int jb = (lane & 16) ? 9 : 0, j0 = jb + ((lane & 8) ? 4 : 0) + ((lane & 4) ? 2 : 0); \
            const uint32_t sa = sb + OFF_SUM + (w * 4 + warp) * 288 + (lane & 3) * 72; \
            sts32(sa + j0 * 4, r3[0]); sts32(sa + j0 * 4 + 4, r3[1]); sts32(sa + (jb + 8) * 4, r3[2]); \
            if (t128 < 72) sts32(sb + OFF_MAX + (hodd ^ 1) * 576 + w * 288 + t128 * 4, 0xff800000u); \
            bar_arrive<4, 288>(); } \
          wg_wait<0>(); \
          RELX(1 + (i), (i) > 1 && last && !(sh && (i) == 2)); \
        } \
        if (w) { \
          if ((i) > 0 && (i) < 3) bar_arrive<10 - ((i) & 1), 256>(); \
          bar_sync<6, 256>(); \
          if ((i) < 3) STORE_P((i) < 3 ? (i) + 1 : 1); \
        } \
        if ((i) > 0) WAITF(v_, (i) == 3); \
        if (w ? (i) < 3 : (i) > 0) fence_async_smem(); \
        if (!w && (i) > 0) bar_sync<5, 256>(); \
        if ((i) > 0) fence_regs(o); \
        wg_fence(); \
        if ((i) == 0) mma_init<1, v_ * PAIR, pb_>(o, d0v, d0); else mma<1, v_ * PAIR, pb_>(o, d0v, d0); \
        mma<1, v_ * PAIR + 2048, pb_ + 32>(o, d0v, d0); mma<1, v_ * PAIR + 4096, pb_ + 64>(o, d0v, d0); mma<1, v_ * PAIR + 6144, pb_ + 96>(o, d0v, d0); \
        mma<1, v_ * PAIR + 8192, pb_ + SLOT>(o, d0v, d0);       mma<1, v_ * PAIR + 10240, pb_ + SLOT + 32>(o, d0v, d0); \
        mma<1, v_ * PAIR + 12288, pb_ + SLOT + 64>(o, d0v, d0); mma<1, v_ * PAIR + 14336, pb_ + SLOT + 96>(o, d0v, d0); \
        wg_commit(); \
        TURN_PASS(); \
        if ((i) < 3) { sched_sep(P.zero); \
            \
          if ((i) < 2) { _Pragma("unroll") for (int r_ = (i) * 18; r_ < (i) * 18 + 18; r_++) { sp[2][r_] = ex2_bf16x2(sp[2][r_]); asm volatile("" : "+r"(sp[2][r_])); } } \
          else { _Pragma("unroll") for (int r_ = 0; r_ < 18; r_++) \
              asm volatile("{\n.reg .b32 t;\nadd.rn.bf16x2 t, %1, %2;\nadd.rn.bf16x2 %0, %0, t;\n}\n" : "+r"(l2[r_]) : "r"(sp[2][2*r_]), "r"(sp[2][2*r_+1])); } \
          sched_sep(P.zero); } } while (0)
      PVSTEP(0);
      PVSTEP(1);
      PVSTEP(2);
      PVSTEP(3);
      fph ^= 0x18u;
      wg_wait<0>();
      fence_regs(o);
      RELX(2, last); REL(1);
      #define LOAD_IV() float4 iv[9]; if (w) bar_sync<8, 160>(); else bar_sync<7, 160>(); \
          _Pragma("unroll") for (int j = 0; j < 9; j++) iv[j] = lds128(sb + OFF_INV + (lane & 3) * 144 + j * 16)
      if (last) {
        LOAD_IV();
        if (!w) bar_sync<5, 256>();
        O_NORM_STSM();
        break;
      }
      if (sh && h == 2) { WAITF(5, 0); fph ^= 0x20u; }
      LOAD_IV();
      PHASE_S(sched_sep(P.zero); O_NORM_STSM(); sched_sep(P.zero), true);
    }
    {
      float a0[72];
      #pragma unroll
      for (int i = 0; i < 72; i++) a0[i] = 0.f;
      const uint32_t dg = (lane >> 3) == (lane & 3) ? ((lane & 4) ? 0x3f800000u : 0x00003f80u) : 0u;
      const uint32_t db = d0 + w * (SLOT / 16);
      const uint32_t g0 = warp == 0 ? dg : 0u, g1 = warp == 1 ? dg : 0u, g2 = warp == 2 ? dg : 0u, g3 = warp == 3 ? dg : 0u;
      #define FOLD(p) do { fence_regs(a0); wg_fence(); \
          mma_rs<(p) * PAIR>(a0, g0, db); mma_rs<(p) * PAIR + 32>(a0, g1, db); mma_rs<(p) * PAIR + 64>(a0, g2, db); mma_rs<(p) * PAIR + 96>(a0, g3, db); \
          wg_commit(); } while (0)
      FOLD(5); STG_ARRIVE(); wg_wait<0>(); fence_regs(a0); REL(5);
      if (sh) { WAITF(3, 0); FOLD(3); wg_wait<0>(); fence_regs(a0); REL(3); fph ^= 0x08u; }
      int sprev = 0;
      XLOOP(a0, 0, 48 - 16 * sh, 1 + sh, true);
      STG_FREE();
      wg_wait<0>();
      fence_regs(a0);
      store_acc_T(a0, st_base);
      STG_ARRIVE();
    }
    cluster_sync();
    #undef lane
    #undef warp
  }
}

typedef CUresult (*PFN_enc)(CUtensorMap*, CUtensorMapDataType, cuuint32_t, void*, const cuuint64_t*, const cuuint64_t*,
                            const cuuint32_t*, const cuuint32_t*, CUtensorMapInterleave, CUtensorMapSwizzle,
                            CUtensorMapL2promotion, CUtensorMapFloatOOBfill);

void enc2d(PFN_enc enc, CUtensorMap* m, const void* p, uint64_t cols, uint64_t rows, uint32_t box_rows) {
  cuuint64_t dims[2] = {cols, rows}; cuuint64_t st[1] = {cols * 2};
  cuuint32_t box[2] = {64, box_rows}; cuuint32_t es[2] = {1, 1};
  enc(m, CU_TENSOR_MAP_DATA_TYPE_BFLOAT16, 2, (void*)p, dims, st, box, es, CU_TENSOR_MAP_INTERLEAVE_NONE,
      CU_TENSOR_MAP_SWIZZLE_128B, CU_TENSOR_MAP_L2_PROMOTION_L2_128B, CU_TENSOR_MAP_FLOAT_OOB_FILL_NONE);
}
void enc3d(PFN_enc enc, CUtensorMap* m, const void* p, uint64_t cols, uint64_t rows, uint32_t box_rows) {
  cuuint64_t dims[3] = {64, rows, cols / 64}; cuuint64_t st[2] = {cols * 2, 128};
  cuuint32_t box[3] = {64, box_rows, 2}; cuuint32_t es[3] = {1, 1, 1};
  enc(m, CU_TENSOR_MAP_DATA_TYPE_BFLOAT16, 3, (void*)p, dims, st, box, es, CU_TENSOR_MAP_INTERLEAVE_NONE,
      CU_TENSOR_MAP_SWIZZLE_128B, CU_TENSOR_MAP_L2_PROMOTION_L2_256B, CU_TENSOR_MAP_FLOAT_OOB_FILL_NONE);
}

}

extern "C" void kernel_launch(void* const* d_in, const int* in_sizes, int n_in, void* d_out, int out_size) {
  (void)in_sizes; (void)n_in; (void)out_size;
  void* fn = nullptr; cudaDriverEntryPointQueryResult q;
  cudaGetDriverEntryPoint("cuTensorMapEncodeTiled", &fn, cudaEnableDefault, &q);
  PFN_enc enc = (PFN_enc)fn;
  void* oscr = nullptr; cudaGetSymbolAddress(&oscr, g_oscr);
  Params P;
  for (int i = 0; i < 2; i++) {
    enc2d(enc, &P.x[i], d_in[5*i + 0], 1024, TOK, 72);
    enc3d(enc, &P.k[i], d_in[5*i + 1], 128, 8 * 32 * 512, 128);
    enc3d(enc, &P.v[i], d_in[5*i + 2], 128, 8 * 32 * 512, 128);
    enc3d(enc, &P.wq[i], d_in[5*i + 3], 4096, 1024, 64);
    enc3d(enc, &P.wo[i], d_in[5*i + 4], 1024, 4096, 64);
    P.kptr[i] = (const char*)d_in[5*i + 1];
  }
  enc2d(enc, &P.os, oscr, 4096, 2 * TOK, 72);
  enc2d(enc, &P.oss, oscr, 4096, 2 * TOK, 24);
  enc2d(enc, &P.out, d_out, 2048, TOK, SQ);
  P.zero = 0;
  cudaFuncSetAttribute(fused_kernel, cudaFuncAttributeMaxDynamicSharedMemorySize, SMEM_BYTES);
  cudaLaunchConfig_t cfg = {};
  cfg.gridDim = dim3(NCTA); cfg.blockDim = dim3(384); cfg.dynamicSmemBytes = SMEM_BYTES; cfg.stream = cudaStreamPerThread;
  cudaLaunchAttribute at[1];
  at[0].id = cudaLaunchAttributeClusterDimension; at[0].val.clusterDim.x = 2; at[0].val.clusterDim.y = 1; at[0].val.clusterDim.z = 1;
  cfg.attrs = at; cfg.numAttrs = 1;
  cudaLaunchKernelEx(&cfg, fused_kernel, P);
}
```

```cpp
#include <cuda_runtime.h>
#include <cuda.h>
#include <cuda_bf16.h>
#include <stdint.h>

namespace {

constexpr int SQ = 144;
constexpr int TOK = 1152;
constexpr int SLOT = 18432;
constexpr int PAIR = 2 * SLOT;
constexpr int OFF_BAR = 6 * PAIR;
constexpr int OFF_MAX = OFF_BAR + 256;
constexpr int OFF_SUM = OFF_MAX + 2 * 576;
constexpr int OFF_INV = OFF_SUM + 8 * 288;
constexpr int SMEM_BYTES = OFF_INV + 576 + 1024;
constexpr int NCTA = 128;

struct alignas(64) Params {
  CUtensorMap x[2], wq[2], k[2], v[2], wo[2], os, oss, out;
  const char* kptr[2];
  uint32_t zero;
};

__device__ __nv_bfloat16 g_oscr[2 * TOK * 4096];
__device__ uint4 g_park[NCTA * 2 * (PAIR / 16)];
__device__ unsigned int g_cnt[64];
__device__ unsigned int g_done;

__device__ __forceinline__ uint32_t smem_u32(const void* p) { return (uint32_t)__cvta_generic_to_shared(p); }
__device__ __forceinline__ void mbar_init(uint32_t bar, int cnt) {
  asm volatile("mbarrier.init.shared::cta.b64 [%0], %1;" :: "r"(bar), "r"(cnt));
}
__device__ __forceinline__ void mbar_arrive(uint32_t bar, uint32_t cnt = 1) {
  asm volatile("mbarrier.arrive.shared::cta.b64 _, [%0], %1;" :: "r"(bar), "r"(cnt) : "memory");
}
__device__ __forceinline__ void mbar_wait(uint32_t bar, uint32_t parity) {
  asm volatile("{\n.reg .pred p;\n.reg .u32 c;\nmov.u32 c, 0;\n"
    "LAB_WAIT:\n"
    "mbarrier.try_wait.parity.shared::cta.b64 p, [%0], %1;\n"
    "@p bra DONE;\n"
    "add.u32 c, c, 1;\n"
    "setp.lt.u32 p, c, 400000;\n"
    "@p bra LAB_WAIT;\n"
    "DONE:\n}\n" :: "r"(bar), "r"(parity) : "memory");
}
#define ELECT_BEGIN "{\n.reg .pred p;\nelect.sync _|p, 0xffffffff;\n"
__device__ __forceinline__ void tma2d_mc(uint32_t dst, const CUtensorMap* map, int c0, int c1, uint32_t bar) {
  asm volatile(ELECT_BEGIN
    "@p cp.async.bulk.tensor.2d.shared::cluster.global.mbarrier::complete_tx::bytes.multicast::cluster [%0], [%1, {%3, %4}], [%2], %5;\n}\n"
    :: "r"(dst), "l"(map), "r"(bar), "r"(c0), "r"(c1), "h"((uint16_t)3) : "memory");
}
__device__ __forceinline__ void tma3d(uint32_t dst, const CUtensorMap* map, int c1, int c2, uint32_t bar, uint32_t bytes, uint64_t pol) {
  asm volatile(ELECT_BEGIN "@p mbarrier.arrive.expect_tx.shared::cta.b64 _, [%2], %6;\n"
    "@p cp.async.bulk.tensor.3d.shared::cluster.global.mbarrier::complete_tx::bytes.L2::cache_hint [%0], [%1, {%3, %4, %5}], [%2], %7;\n}\n"
    :: "r"(dst), "l"(map), "r"(bar), "r"(0), "r"(c1), "r"(c2), "r"(bytes), "l"(pol) : "memory");
}
__device__ __forceinline__ void bulk_load_pair(uint32_t dst, const void* src, uint32_t bar) {
  asm volatile(ELECT_BEGIN "@p mbarrier.arrive.expect_tx.shared::cta.b64 _, [%2], %3;\n"
    "@p cp.async.bulk.shared::cluster.global.mbarrier::complete_tx::bytes [%0], [%1], %3, [%2];\n}\n"
    :: "r"(dst), "l"(src), "r"(bar), "r"(PAIR) : "memory");
}
__device__ __forceinline__ void tma2d_store(const CUtensorMap* map, int c0, int c1, uint32_t src) {
  asm volatile("cp.async.bulk.tensor.2d.global.shared::cta.bulk_group [%0, {%1, %2}], [%3];"
    :: "l"(map), "r"(c0), "r"(c1), "r"(src) : "memory");
}
__device__ __forceinline__ uint64_t evict_first_policy() {
  uint64_t pol; asm volatile("createpolicy.fractional.L2::evict_first.b64 %0, 1.0;" : "=l"(pol)); return pol;
}
__device__ __forceinline__ void sched_sep(uint32_t zero) {
  asm volatile("{\n.reg .pred p;\n.reg .u32 c;\nSEP_L:\n.pragma \"nounroll\";\nmov.u32 c, %%clock;\nsetp.lt.u32 p, c, %0;\n@p bra SEP_L;\n}\n" :: "r"(zero) : "memory");
}
__device__ __forceinline__ void wg_fence() { asm volatile("wgmma.fence.sync.aligned;" ::: "memory"); }
__device__ __forceinline__ void wg_commit() { asm volatile("wgmma.commit_group.sync.aligned;" ::: "memory"); }
template<int N> __device__ __forceinline__ void wg_wait() { asm volatile("wgmma.wait_group.sync.aligned %0;" :: "n"(N) : "memory"); }
__device__ __forceinline__ void fence_regs(float (&d)[72]) {
  #pragma unroll
  for (int i = 0; i < 72; i++) asm volatile("" : "+f"(d[i]) :: "memory");
}
__device__ __forceinline__ void fence_async_smem() { asm volatile("fence.proxy.async.shared::cta;" ::: "memory"); }
template<int ID, int N> __device__ __forceinline__ void bar_sync() { asm volatile("bar.sync %0, %1;" :: "n"(ID), "n"(N) : "memory"); }
template<int ID, int N> __device__ __forceinline__ void bar_arrive() { asm volatile("bar.arrive %0, %1;" :: "n"(ID), "n"(N) : "memory"); }
__device__ __forceinline__ void cluster_sync() {
  asm volatile("barrier.cluster.arrive.relaxed.aligned;\nbarrier.cluster.wait.aligned;" ::: "memory");
}
__device__ __forceinline__ uint32_t pack_bf16(float lo, float hi) {
  uint32_t r; asm("cvt.rn.bf16x2.f32 %0, %1, %2;" : "=r"(r) : "f"(hi), "f"(lo)); return r;
}
__device__ __forceinline__ uint32_t max_bf16x2(uint32_t a, uint32_t b) {
  uint32_t r; asm("max.bf16x2 %0, %1, %2;" : "=r"(r) : "r"(a), "r"(b)); return r;
}
__device__ __forceinline__ uint32_t add_bf16x2(uint32_t a, uint32_t b) {
  uint32_t r; asm("add.rn.bf16x2 %0, %1, %2;" : "=r"(r) : "r"(a), "r"(b)); return r;
}
__device__ __forceinline__ uint32_t sub_bf16x2(uint32_t a, uint32_t b) {
  uint32_t r; asm("sub.rn.bf16x2 %0, %1, %2;" : "=r"(r) : "r"(a), "r"(b)); return r;
}
__device__ __forceinline__ uint32_t ex2_bf16x2(uint32_t a) {
  uint32_t r;
  asm("{\n.reg .b32 t;\nex2.approx.ftz.bf16x2 t, %1;\nmax.NaN.bf16x2 %0, t, %2;\n}\n" : "=r"(r) : "r"(a), "r"(0u));
  return r;
}
__device__ __forceinline__ void ex2_halves(uint32_t a, uint16_t& lo, uint16_t& hi) {
  asm volatile("{\n.reg .b16 l, h;\nmov.b32 {l, h}, %2;\nex2.approx.ftz.bf16 %0, l;\nex2.approx.ftz.bf16 %1, h;\n}\n" : "=h"(lo), "=h"(hi) : "r"(a));
}
__device__ __forceinline__ uint32_t pack_halves(uint16_t lo, uint16_t hi) {
  uint32_t r; asm volatile("mov.b32 %0, {%1, %2};" : "=r"(r) : "h"(lo), "h"(hi)); return r;
}
__device__ __forceinline__ uint32_t pack_halves_pin(uint16_t lo, uint16_t hi) {
  uint32_t r; asm volatile("{\n.reg .b32 t;\nmov.b32 t, {%1, %2};\nmax.NaN.bf16x2 %0, t, %3;\n}\n" : "=r"(r) : "h"(lo), "h"(hi), "r"(0u)); return r;
}
__device__ __forceinline__ float bf_lo(uint32_t v) { return __uint_as_float(v << 16); }
__device__ __forceinline__ float bf_hi(uint32_t v) { return __uint_as_float(v & 0xffff0000u); }
__device__ __forceinline__ void ldsm4t(uint32_t addr, uint32_t& a, uint32_t& b, uint32_t& c, uint32_t& d) {
  asm volatile("ldmatrix.sync.aligned.m8n8.x4.trans.shared.b16 {%0, %1, %2, %3}, [%4];"
    : "=r"(a), "=r"(b), "=r"(c), "=r"(d) : "r"(addr));
}
__device__ __forceinline__ void stsm4t(uint32_t addr, uint32_t a, uint32_t b, uint32_t c, uint32_t d) {
  asm volatile("stmatrix.sync.aligned.m8n8.x4.trans.shared.b16 [%0], {%1, %2, %3, %4};"
    :: "r"(addr), "r"(a), "r"(b), "r"(c), "r"(d));
}
__device__ __forceinline__ float4 lds128(uint32_t addr) {
  float4 v; asm volatile("ld.shared.v4.f32 {%0, %1, %2, %3}, [%4];" : "=f"(v.x), "=f"(v.y), "=f"(v.z), "=f"(v.w) : "r"(addr)); return v;
}
__device__ __forceinline__ void sts32(uint32_t addr, uint32_t v) { asm volatile("st.shared.u32 [%0], %1;" :: "r"(addr), "r"(v) : "memory"); }
__device__ __forceinline__ void red_max_f32(uint32_t addr, float v, bool on) {
  asm volatile("{\n.reg .pred p, q, e;\nsetp.ne.b32 e, %2, 0;\nsetp.ge.and.s32 p|q, %1, 0, e;\n"
               "@p red.shared.max.s32 [%0], %1;\n@q red.shared.min.u32 [%0], %1;\n}\n"
               :: "r"(addr), "r"(__float_as_uint(v)), "r"((uint32_t)on) : "memory");
}

#define ACC_REGS "{%0, %1, %2, %3, %4, %5, %6, %7, %8, %9, %10, %11, %12, %13, %14, %15, %16, %17, %18, %19, %20, %21, %22, %23, %24, %25, %26, %27, %28, %29, %30, %31, %32, %33, %34, %35, %36, %37, %38, %39, %40, %41, %42, %43, %44, %45, %46, %47, %48, %49, %50, %51, %52, %53, %54, %55, %56, %57, %58, %59, %60, %61, %62, %63, %64, %65, %66, %67, %68, %69, %70, %71}"
template<int TA, int OA, int OB>
__device__ __forceinline__ void mma(float (&d)[72], uint32_t a, uint32_t b) {
  asm volatile("{\n.reg .b64 da, db;\n.reg .b32 ta, tb, th;\n"
    "add.u32 ta, %72, %75;\nadd.u32 tb, %73, %76;\nmov.b32 th, 0x40000040;\n"
    "mov.b64 da, {ta, th};\nmov.b64 db, {tb, th};\n"
    "wgmma.mma_async.sync.aligned.m64n144k16.f32.bf16.bf16 " ACC_REGS ", da, db, 1, 1, 1, %74, 0;\n}\n"
    : "+f"(d[0]), "+f"(d[1]), "+f"(d[2]), "+f"(d[3]), "+f"(d[4]), "+f"(d[5]), "+f"(d[6]), "+f"(d[7]), "+f"(d[8]), "+f"(d[9]), "+f"(d[10]), "+f"(d[11]),
      "+f"(d[12]), "+f"(d[13]), "+f"(d[14]), "+f"(d[15]), "+f"(d[16]), "+f"(d[17]), "+f"(d[18]), "+f"(d[19]), "+f"(d[20]), "+f"(d[21]), "+f"(d[22]), "+f"(d[23]),
      "+f"(d[24]), "+f"(d[25]), "+f"(d[26]), "+f"(d[27]), "+f"(d[28]), "+f"(d[29]), "+f"(d[30]), "+f"(d[31]), "+f"(d[32]), "+f"(d[33]), "+f"(d[34]), "+f"(d[35]),
      "+f"(d[36]), "+f"(d[37]), "+f"(d[38]), "+f"(d[39]), "+f"(d[40]), "+f"(d[41]), "+f"(d[42]), "+f"(d[43]), "+f"(d[44]), "+f"(d[45]), "+f"(d[46]), "+f"(d[47]),
      "+f"(d[48]), "+f"(d[49]), "+f"(d[50]), "+f"(d[51]), "+f"(d[52]), "+f"(d[53]), "+f"(d[54]), "+f"(d[55]), "+f"(d[56]), "+f"(d[57]), "+f"(d[58]), "+f"(d[59]),
      "+f"(d[60]), "+f"(d[61]), "+f"(d[62]), "+f"(d[63]), "+f"(d[64]), "+f"(d[65]), "+f"(d[66]), "+f"(d[67]), "+f"(d[68]), "+f"(d[69]), "+f"(d[70]), "+f"(d[71])
    : "r"(a), "r"(b), "n"(TA), "n"(OA / 16), "n"(OB / 16));
}
template<int TA, int OA, int OB>
__device__ __forceinline__ void mma_init(float (&d)[72], uint32_t a, uint32_t b) {
  asm volatile("{\n.reg .b64 da, db;\n.reg .b32 ta, tb, th;\n"
    "add.u32 ta, %72, %75;\nadd.u32 tb, %73, %76;\nmov.b32 th, 0x40000040;\n"
    "mov.b64 da, {ta, th};\nmov.b64 db, {tb, th};\n"
    "wgmma.mma_async.sync.aligned.m64n144k16.f32.bf16.bf16 " ACC_REGS ", da, db, 0, 1, 1, %74, 0;\n}\n"
    : "=f"(d[0]), "=f"(d[1]), "=f"(d[2]), "=f"(d[3]), "=f"(d[4]), "=f"(d[5]), "=f"(d[6]), "=f"(d[7]), "=f"(d[8]), "=f"(d[9]), "=f"(d[10]), "=f"(d[11]),
      "=f"(d[12]), "=f"(d[13]), "=f"(d[14]), "=f"(d[15]), "=f"(d[16]), "=f"(d[17]), "=f"(d[18]), "=f"(d[19]), "=f"(d[20]), "=f"(d[21]), "=f"(d[22]), "=f"(d[23]),
      "=f"(d[24]), "=f"(d[25]), "=f"(d[26]), "=f"(d[27]), "=f"(d[28]), "=f"(d[29]), "=f"(d[30]), "=f"(d[31]), "=f"(d[32]), "=f"(d[33]), "=f"(d[34]), "=f"(d[35]),
      "=f"(d[36]), "=f"(d[37]), "=f"(d[38]), "=f"(d[39]), "=f"(d[40]), "=f"(d[41]), "=f"(d[42]), "=f"(d[43]), "=f"(d[44]), "=f"(d[45]), "=f"(d[46]), "=f"(d[47]),
      "=f"(d[48]), "=f"(d[49]), "=f"(d[50]), "=f"(d[51]), "=f"(d[52]), "=f"(d[53]), "=f"(d[54]), "=f"(d[55]), "=f"(d[56]), "=f"(d[57]), "=f"(d[58]), "=f"(d[59]),
      "=f"(d[60]), "=f"(d[61]), "=f"(d[62]), "=f"(d[63]), "=f"(d[64]), "=f"(d[65]), "=f"(d[66]), "=f"(d[67]), "=f"(d[68]), "=f"(d[69]), "=f"(d[70]), "=f"(d[71])
    : "r"(a), "r"(b), "n"(TA), "n"(OA / 16), "n"(OB / 16));
}
template<int OB>
__device__ __forceinline__ void mma_rs(float (&d)[72], uint32_t diag, uint32_t b) {
  asm volatile("{\n.reg .b64 db;\n.reg .b32 tb, th, z;\n"
    "add.u32 tb, %73, %74;\nmov.b32 th, 0x40000040;\nmov.b32 z, 0;\nmov.b64 db, {tb, th};\n"
    "wgmma.mma_async.sync.aligned.m64n144k16.f32.bf16.bf16 " ACC_REGS ", {%72, z, z, %72}, db, 1, 1, 1, 0;\n}\n"
    : "+f"(d[0]), "+f"(d[1]), "+f"(d[2]), "+f"(d[3]), "+f"(d[4]), "+f"(d[5]), "+f"(d[6]), "+f"(d[7]), "+f"(d[8]), "+f"(d[9]), "+f"(d[10]), "+f"(d[11]),
      "+f"(d[12]), "+f"(d[13]), "+f"(d[14]), "+f"(d[15]), "+f"(d[16]), "+f"(d[17]), "+f"(d[18]), "+f"(d[19]), "+f"(d[20]), "+f"(d[21]), "+f"(d[22]), "+f"(d[23]),
      "+f"(d[24]), "+f"(d[25]), "+f"(d[26]), "+f"(d[27]), "+f"(d[28]), "+f"(d[29]), "+f"(d[30]), "+f"(d[31]), "+f"(d[32]), "+f"(d[33]), "+f"(d[34]), "+f"(d[35]),
      "+f"(d[36]), "+f"(d[37]), "+f"(d[38]), "+f"(d[39]), "+f"(d[40]), "+f"(d[41]), "+f"(d[42]), "+f"(d[43]), "+f"(d[44]), "+f"(d[45]), "+f"(d[46]), "+f"(d[47]),
      "+f"(d[48]), "+f"(d[49]), "+f"(d[50]), "+f"(d[51]), "+f"(d[52]), "+f"(d[53]), "+f"(d[54]), "+f"(d[55]), "+f"(d[56]), "+f"(d[57]), "+f"(d[58]), "+f"(d[59]),
      "+f"(d[60]), "+f"(d[61]), "+f"(d[62]), "+f"(d[63]), "+f"(d[64]), "+f"(d[65]), "+f"(d[66]), "+f"(d[67]), "+f"(d[68]), "+f"(d[69]), "+f"(d[70]), "+f"(d[71])
    : "r"(diag), "r"(b), "n"(OB / 16));
}

__device__ __forceinline__ void store_acc_T(const float (&d)[72], uint32_t addr) {
  #pragma unroll
  for (int j = 0; j < 18; j += 2)
    stsm4t(addr + j * 1024, pack_bf16(d[4*j], d[4*j+1]), pack_bf16(d[4*j+2], d[4*j+3]),
           pack_bf16(d[4*j+4], d[4*j+5]), pack_bf16(d[4*j+6], d[4*j+7]));
}

template<bool IS_MAX>
__device__ __forceinline__ void warp_col_reduce(const uint32_t (&v)[18], uint32_t (&r3)[3], int lane) {
  #define OP(a, b) (IS_MAX ? max_bf16x2(a, b) : add_bf16x2(a, b))
  const bool b4 = lane & 16, b3 = lane & 8, b2 = lane & 4;
  uint32_t r1[9], r2[5];
  #pragma unroll
  for (int k = 0; k < 9; k++) {
    const uint32_t snd = b4 ? v[k] : v[k+9], kp = b4 ? v[k+9] : v[k];
    r1[k] = OP(kp, __shfl_xor_sync(0xffffffff, snd, 16));
  }
  #pragma unroll
  for (int k = 0; k < 4; k++) {
    const uint32_t snd = b3 ? r1[k] : r1[k+4], kp = b3 ? r1[k+4] : r1[k];
    r2[k] = OP(kp, __shfl_xor_sync(0xffffffff, snd, 8));
  }
  r2[4] = OP(r1[8], __shfl_xor_sync(0xffffffff, r1[8], 8));
  #pragma unroll
  for (int k = 0; k < 2; k++) {
    const uint32_t snd = b2 ? r2[k] : r2[k+2], kp = b2 ? r2[k+2] : r2[k];
    r3[k] = OP(kp, __shfl_xor_sync(0xffffffff, snd, 4));
  }
  r3[2] = OP(r2[4], __shfl_xor_sync(0xffffffff, r2[4], 4));
  #undef OP
}

constexpr uint32_t XLAP = 0x12435u, GLAP0 = 0x53241u, GLAP = 0x54321u;
struct Seg { int isq, head_or_k0, n, np; uint32_t lap, lap2; int lap0; };
__device__ __forceinline__ Seg seg_info(int n, int sh) {
  Seg s;
  s.isq = n <= 4 - sh;
  s.head_or_k0 = n == 0 ? 3 : (s.isq ? n - 1 : (n - 5 + sh) * 16);
  s.np = n == 6 ? 1 + sh : 0;
  s.n = n == 6 ? 49 - 15 * sh : 16;
  const bool g = n >= 2 && n <= 5;
  s.lap = g ? GLAP0 : XLAP;
  s.lap2 = g ? GLAP : XLAP;
  s.lap0 = n == 0 ? 4 : 0;
  return s;
}

__global__ void __launch_bounds__(384, 1) fused_kernel(const __grid_constant__ Params P) {
  extern __shared__ __align__(1024) char smem_raw[];
  const uint32_t sb = (smem_u32(smem_raw) + 1023u) & ~1023u;
  const uint32_t full0 = sb + OFF_BAR;
  const uint32_t emptyB = full0 + 48;
  const uint32_t emptyA = full0 + 192;
  const uint32_t stg0 = full0 + 96, maxbar = full0 + 104, stgfree = full0 + 112, ordy = full0 + 144;
  const uint32_t kvcnt = full0 + 128;
  const int tid = threadIdx.x;
  const int wg = __shfl_sync(0xffffffff, tid >> 7, 0);
  uint32_t rank; asm volatile("mov.u32 %0, %%cluster_ctarank;" : "=r"(rank));
  int cl;
  {
    const int c = blockIdx.x >> 1, t = c - 4;
    int set, idx;
    if (c < 4) { set = 1; idx = c; }
    else if (t < 32) { set = 2 * (t & 7); idx = t >> 3; }
    else { set = 2 * (1 + (t - 32) % 7) + 1; idx = (t - 32) / 7; }
    cl = ((set & 1) << 5) | ((set >> 1) << 2) | idx;
  }
  const int blk = cl >> 5, b = cl & 7, sub = ((cl >> 3) & 3) * 2 + rank, sh = blk;
  uint4* const park = g_park + (cl * 2 + rank) * (2 * (PAIR / 16));

  if (tid == 0) {
    for (int i = 0; i < 6; i++) { mbar_init(full0 + 8*i, 1); mbar_init(emptyB + 8*i, 4); mbar_init(emptyA + 8*i, 2); }
    mbar_init(stg0, 8); mbar_init(maxbar, 8); mbar_init(stgfree, 1);
    for (int i = 0; i < 4; i++) mbar_init(ordy + 8*i, 1);
    asm volatile("fence.mbarrier_init.release.cluster;" ::: "memory");
  }
  if (tid < 288) sts32(sb + OFF_MAX + tid * 4, 0xff800000u);
  if (tid == 300) sts32(kvcnt, 0u);
  __syncthreads();
  cluster_sync();

  if (wg == 2) {
    asm volatile("setmaxnreg.dec.sync.aligned.u32 24;");
    const int warp = __shfl_sync(0xffffffff, (tid >> 5) & 3, 0);
    const int lane = tid & 31;
    const uint32_t ebar = warp == 0 ? emptyA : emptyB;
    #define ACQ(s) do { mbar_wait(ebar + 8*(s), (eph >> (s)) & 1); eph ^= 1u << (s); } while (0)
    if (warp == 0) {
      uint32_t eph = 0x3Fu;
      const uint64_t pol = evict_first_policy();
      int nkv = 0;
      uint32_t tlast = (uint32_t)clock64();
      #pragma unroll 1
      for (int n = 1 - sh; n < 7; n++) {
        Seg sg = seg_info(n, sh);
        const CUtensorMap* map = sg.isq ? &P.wq[blk] : &P.wo[blk];
        const int k0 = sg.isq ? 0 : sg.head_or_k0, col = (sg.isq ? sg.head_or_k0 * 8 + sub : sub) * 2;
        int lp = sg.lap0;
        #pragma unroll 1
        for (int j = 0; j < sg.n; j++) {
          const int s = (sg.lap >> (lp * 4)) & 15;
          const int kk = k0 + j - sg.np;
          if (j < sg.np) {
            if (j == 1) { mbar_wait(ordy + 16, 0); ACQ(s); bulk_load_pair(sb + s * PAIR, park, full0 + 8*s); }
          } else {
            ACQ(s);
            tma3d(sb + s * PAIR + SLOT, map, kk * 64, col, full0 + 8*s, 18432 + 16384, pol);
          }
          if (++lp == 5) { lp = 0; sg.lap = sg.lap2; }
        }
        #pragma unroll 1
        for (int q = (n >= 2 && n <= 5 ? 0 : 4); q < (n >= 1 && n <= 4 ? 8 : 4); q++) {
          if (sh && n == 4 && q == 4) { mbar_wait(ordy, 0); ACQ(5); bulk_load_pair(sb + 5 * PAIR, park + PAIR / 16, full0 + 40); }
          const int s = (0x32432432u >> (q * 4)) & 15;
          const int head = (q < 4 ? n - 2 : n - 1) * 8 + sub;
          ACQ(s);
          { const int gap = q == 1 ? 1500 : (q == 2 ? 1250 : 0);
            while ((int)((uint32_t)clock64() - tlast) < gap) __nanosleep(30);
            tlast = (uint32_t)clock64(); }
          tma3d(sb + s * PAIR, q < 4 ? &P.v[blk] : &P.k[blk], (b * 32 + head) * 512 + ((q < 4 ? q : q + 1) & 3) * 128, 0, full0 + 8*s, 32768, pol);
          nkv++;
          asm volatile("st.volatile.shared.u32 [%0], %1;" :: "r"(kvcnt), "r"(nkv) : "memory");
        }
      }
    } else if (warp == 1) {
      uint32_t eph = 0x3Fu;
      #pragma unroll 1
      for (int n = 1 - sh; n < 7; n++) {
        Seg sg = seg_info(n, sh);
        const CUtensorMap* map = sg.isq ? &P.x[blk] : &P.os;
        const int row = (sg.isq ? 0 : blk * TOK) + b * SQ + rank * 72, k0 = sg.isq ? 0 : sg.head_or_k0;
        int lp = sg.lap0;
        #pragma unroll 1
        for (int j = 0; j < sg.n; j++) {
          const int s = (sg.lap >> (lp * 4)) & 15;
          if (j >= sg.np) {
            const int kk = k0 + j - sg.np;
            if (!sg.isq && (kk & 15) == 0) mbar_wait(ordy + 8 * (kk >> 4), 0);
            ACQ(s);
            tma2d_mc(sb + s * PAIR + rank * 9216, map, kk * 64, row, full0 + 8*s);
          }
          if (++lp == 5) { lp = 0; sg.lap = sg.lap2; }
        }
      }
    } else if (warp == 2) {
      uint32_t ph = 0;
      #define PARK_STORE(slot, pair) do { if (lane == 0) { mbar_wait(stg0, ph); \
          _Pragma("unroll 1") for (int pc = 0; pc < 12; pc++) \
            asm volatile("cp.async.bulk.global.shared::cta.bulk_group [%0], [%1], %2;" :: "l"(park + (slot) * (PAIR / 16) + pc * 192), "r"(sb + (pair) * PAIR + pc * 3072), "r"(3072) : "memory"); \
          asm volatile("cp.async.bulk.commit_group;" ::: "memory"); \
          asm volatile("cp.async.bulk.wait_group.read 0;" ::: "memory"); \
          if (pair) mbar_arrive(emptyA + 40, 2); else mbar_arrive(stgfree); } \
          ph ^= 1; __syncwarp(); } while (0)
      if (sh) PARK_STORE(1, 0);
      #pragma unroll 1
      for (int n = 0; n < 4; n++) {
        if (n == 2 && sh) PARK_STORE(0, 5);
        bar_sync<4, 288>();
        #pragma unroll
        for (int r = 0; r < 3; r++) {
          const int idx = r * 32 + lane;
          if (idx < 72) {
            float s0 = 0.f, s1 = 0.f;
            #pragma unroll
            for (int ww = 0; ww < 8; ww++) {
              uint32_t v; asm volatile("ld.shared.u32 %0, [%1];" : "=r"(v) : "r"(sb + OFF_SUM + ww * 288 + idx * 4));
              s0 += bf_lo(v); s1 += bf_hi(v);
            }
            asm volatile("st.shared.v2.f32 [%0], {%1, %2};" :: "r"(sb + OFF_INV + idx * 8), "f"(__fdividef(1.f, s0)), "f"(__fdividef(1.f, s1)) : "memory");
          }
        }
        bar_arrive<7, 160>();
        bar_arrive<8, 160>();
        if (lane == 0) {
          mbar_wait(stg0, ph);
          #pragma unroll 1
          for (int pc = 0; pc < 12; pc++)
            tma2d_store(&P.oss, (n * 8 + sub) * 128 + (pc & 1) * 64, blk * TOK + b * SQ + (pc >> 1) * 24, sb + (pc & 1) * SLOT + (pc >> 1) * 3072);
          asm volatile("cp.async.bulk.commit_group;" ::: "memory");
          asm volatile("cp.async.bulk.wait_group.read 0;" ::: "memory");
          mbar_arrive(stgfree);
          asm volatile("cp.async.bulk.wait_group 0;" ::: "memory");
          asm volatile("fence.proxy.async.global;" ::: "memory");
          asm volatile("red.release.gpu.global.add.u32 [%0], %1;" :: "l"(&g_cnt[(blk * 8 + b) * 4 + n]), "r"(1u) : "memory");
        }
        ph ^= 1;
        __syncwarp();
      }
      if (lane == 0) {
        mbar_wait(stg0, ph);
        tma2d_store(&P.out, blk * 1024 + sub * 128, b * SQ, sb);
        tma2d_store(&P.out, blk * 1024 + sub * 128 + 64, b * SQ, sb + SLOT);
        asm volatile("cp.async.bulk.commit_group;" ::: "memory");
        asm volatile("cp.async.bulk.wait_group.read 0;" ::: "memory");
      }
    } else {
      unsigned int epoch;
      asm volatile("ld.relaxed.gpu.global.u32 %0, [%1];" : "=r"(epoch) : "l"(&g_done) : "memory");
      const unsigned int target = 8u * ((epoch >> 7) + 1);
      {
        const char* kp = P.kptr[blk] + (size_t)(b * 32 + sub) * (512 * 256) + lane * 256;
        uint32_t v0 = 0, v1 = 0;
        uint32_t tnext = (uint32_t)clock64() + (sh ? 11000 : 2000);
        int q = 0;
        #pragma unroll 1
        for (int spin = 0; spin < 1000000 && q < 8; spin++) {
          int cnt; asm volatile("ld.volatile.shared.u32 %0, [%1];" : "=r"(cnt) : "r"(kvcnt) : "memory");
          if (q < cnt * 2) q = cnt * 2;
          const uint32_t now = (uint32_t)clock64();
          if ((int)(now - tnext) >= 0 && q < 8) {
            const char* a = kp + ((q + 2) & 7) * 16384;
            asm volatile("st.volatile.shared.u32 [%0], %1;" :: "r"(kvcnt + 8), "r"(v0 ^ v1) : "memory");
            asm volatile("ld.global.L2::256B.u32 %0, [%1];" : "=r"(v0) : "l"(a) : "memory");
            asm volatile("ld.global.L2::256B.u32 %0, [%1];" : "=r"(v1) : "l"(a + 8192) : "memory");
            q++; tnext = now + (sh ? 1400 : 900);
          } else __nanosleep(50);
        }
        asm volatile("st.volatile.shared.u32 [%0], %1;" :: "r"(kvcnt + 8), "r"(v0 ^ v1) : "memory");
      }
      int nrdy = 0;
      #pragma unroll 1
      for (int spin = 0; spin < 1000000 && nrdy < 4; spin++) {
        int cnt; asm volatile("ld.volatile.shared.u32 %0, [%1];" : "=r"(cnt) : "r"(kvcnt) : "memory");
        if (cnt >= nrdy * 8 + 8) {
          unsigned int c; asm volatile("ld.acquire.gpu.global.u32 %0, [%1];" : "=r"(c) : "l"(&g_cnt[(blk * 8 + b) * 4 + nrdy]) : "memory");
          if ((int)(c - target) >= 0) {
            asm volatile("fence.proxy.async.global;" ::: "memory");
            __syncwarp();
            if (lane == 0) mbar_arrive(ordy + 8 * nrdy);
            nrdy++;
          }
        }
        __nanosleep(100);
      }
      if (lane == 0) atomicAdd(&g_done, 1u);
    }
    __syncwarp();
    cluster_sync();
  } else {
    asm volatile("setmaxnreg.inc.sync.aligned.u32 240;");
    const int w = wg;
    int t128 = tid & 127;
    asm volatile("" : "+r"(t128));
    #define lane (t128 & 31)
    #define warp (t128 >> 5)
    const uint32_t st_base = sb + w * SLOT + (uint32_t)(((lane >> 4) * 8 + (lane & 7)) * 128 + (((2 * warp + ((lane >> 3) & 1)) ^ (lane & 7)) << 4));
    const uint32_t d0 = ((sb & 0x3FFFF) >> 4) | (64u << 16);
    const uint32_t d0w = d0 + w * 512, d0v = d0 + w * 1024;
    uint32_t rel_addr; asm("mapa.shared::cluster.u32 %0, %1, %2;" : "=r"(rel_addr) : "r"(t128 == 0 ? emptyA : emptyB), "r"(t128 == 0 ? rank : (uint32_t)(t128 & 1)));
    #define WAITF(s, flip) mbar_wait(full0 + 8*(s), ((fph >> (s)) & 1) ^ (flip))
    #define RELX(s, all) asm volatile("{\n.reg .pred p;\nsetp.lt.u32 p, %1, %2;\n@p mbarrier.arrive.relaxed.cluster.shared::cluster.b64 _, [%0];\n}\n" :: "r"(rel_addr + 8*(s)), "r"(t128), "r"((all) ? 3 : 1) : "memory")
    #define REL(s) RELX(s, true)
    #define STG_ARRIVE() do { fence_async_smem(); __syncwarp(); if (lane == 0) mbar_arrive(stg0); } while (0)
    #define STG_FREE() do { mbar_wait(stgfree, sfp); sfp ^= 1; } while (0)
    #define TURN_WAIT() do { if (w) bar_sync<6, 256>(); else bar_sync<5, 256>(); } while (0)
    #define TURN_PASS() do { if (w) bar_arrive<5, 256>(); else bar_arrive<6, 256>(); } while (0)
    #define GMMA(acc, da, db, O, first) do { if (!(first)) fence_regs(acc); wg_fence(); \
        if (first) mma_init<1, (O) + SLOT, (O)>(acc, da, db); else mma<1, (O) + SLOT, (O)>(acc, da, db); \
        mma<1, (O) + SLOT + 2048, (O) + 32>(acc, da, db); mma<1, (O) + SLOT + 4096, (O) + 64>(acc, da, db); \
        mma<1, (O) + SLOT + 6144, (O) + 96>(acc, da, db); wg_commit(); } while (0)
    const float cs = 0.08838834764831845f * 1.4426950408889634f;
    uint32_t fph = 0, sfp = 0;
    #define XLOOP(a0, j0, n, lp0, tail_local) do { int lp = lp0; \
        _Pragma("unroll 1") for (int j = j0; j < n; j++) { \
          const int s_ = (XLAP >> (lp * 4)) & 15; \
          WAITF(s_, 0); fph ^= 1u << s_; \
          const uint32_t off = s_ * (PAIR / 16); \
          GMMA(a0, d0w + off, d0 + off, 0, false); \
          wg_wait<1>(); \
          if (j > j0) RELX(sprev, !((tail_local) && j > n - 5 && sprev >= 2 && sprev <= 4)); \
          sprev = s_; \
          if (++lp == 5) lp = 0; \
        } } while (0)
    #pragma unroll 1
    for (int h = -sh; h <= 0; h++) {
      float a0[72];
      #pragma unroll
      for (int i = 0; i < 72; i++) a0[i] = 0.f;
      int sprev = 0;
      XLOOP(a0, 0, 16, h ? 4 : 0, h == 0);
      wg_wait<0>();
      fence_regs(a0);
      if (h == 0) bar_sync<3, 256>(); else REL(sprev);
      #pragma unroll
      for (int i = 0; i < 72; i++) a0[i] *= cs;
      store_acc_T(a0, st_base + (h == 0 ? 5 * PAIR : 0));
      fence_async_smem();
      if (h != 0) { __syncwarp(); if (lane == 0) mbar_arrive(stg0); }
    }
    if (w) bar_arrive<5, 256>();
    uint32_t sp[3][36];
    uint32_t mx[18];
        #define PACK(s, i) do { _Pragma("unroll") for (int j = 0; j < 18; j++) { \
            sp[i][2*j] = pack_bf16(s[4*j], s[4*j+1]); sp[i][2*j+1] = pack_bf16(s[4*j+2], s[4*j+3]); \
            const uint32_t m2 = max_bf16x2(sp[i][2*j], sp[i][2*j+1]); \
            mx[j] = (i) ? max_bf16x2(mx[j], m2) : m2; \
            asm volatile("" : "+r"(sp[i][2*j]), "+r"(sp[i][2*j+1]), "+r"(mx[j]) :: "memory"); } } while (0)
        #define SISSUE(s, p, fin) do { TURN_WAIT(); wg_fence(); \
            mma_init<0, (p) * PAIR, 5 * PAIR>(s, d0w, d0);      mma<0, (p) * PAIR + 32, 5 * PAIR + 32>(s, d0w, d0); \
            mma<0, (p) * PAIR + 64, 5 * PAIR + 64>(s, d0w, d0); mma<0, (p) * PAIR + 96, 5 * PAIR + 96>(s, d0w, d0); \
            mma<0, (p) * PAIR + 16384, 5 * PAIR + SLOT>(s, d0w, d0);           mma<0, (p) * PAIR + 16384 + 32, 5 * PAIR + SLOT + 32>(s, d0w, d0); \
            mma<0, (p) * PAIR + 16384 + 64, 5 * PAIR + SLOT + 64>(s, d0w, d0); mma<0, (p) * PAIR + 16384 + 96, 5 * PAIR + SLOT + 96>(s, d0w, d0); \
            wg_commit(); if (!(fin) || !w) TURN_PASS(); } while (0)
    #define O_NORM_STSM() do { _Pragma("unroll") for (int c_ = 0; c_ < 9; c_++) \
        stsm4t(st_base + c_ * 2048, pack_bf16(o[8*c_] * iv[c_].x, o[8*c_+1] * iv[c_].y), pack_bf16(o[8*c_+2] * iv[c_].x, o[8*c_+3] * iv[c_].y), \
               pack_bf16(o[8*c_+4] * iv[c_].z, o[8*c_+5] * iv[c_].w), pack_bf16(o[8*c_+6] * iv[c_].z, o[8*c_+7] * iv[c_].w)); } while (0)
    #define PHASE_S(with_o, wait_stg) do { \
        float sa[72], sc[72], s[72]; \
        WAITF(3, 0); \
        SISSUE(sa, 3, false); \
        with_o; \
        wg_wait<0>(); fence_regs(sa); RELX(3, false); \
        WAITF(4, 0); \
        SISSUE(sc, 4, false); \
        sched_sep(P.zero); \
        PACK(sa, 0); \
        if (sizeof(#with_o) > 1) STG_ARRIVE(); \
        sched_sep(P.zero); \
        wg_wait<0>(); fence_regs(sc); REL(4); \
        PACK(sc, 1); \
        WAITF(2, 0); \
        SISSUE(sc, 2, false); \
        wg_wait<0>(); fence_regs(sc); REL(2); \
        PACK(sc, 2); \
        WAITF(3, 1); \
        SISSUE(s, 3, true); \
        if (wait_stg) STG_FREE(); \
        wg_wait<0>(); fence_regs(s); REL(3); REL(5); \
        _Pragma("unroll") for (int c = 0; c < 9; c++) { \
          const uint32_t k0 = pack_bf16(s[8*c], s[8*c+1]), k1 = pack_bf16(s[8*c+2], s[8*c+3]); \
          const uint32_t k2 = pack_bf16(s[8*c+4], s[8*c+5]), k3 = pack_bf16(s[8*c+6], s[8*c+7]); \
          stsm4t(st_base + c * 2048, k0, k1, k2, k3); \
          mx[2*c] = max_bf16x2(mx[2*c], max_bf16x2(k0, k1)); \
          mx[2*c+1] = max_bf16x2(mx[2*c+1], max_bf16x2(k2, k3)); \
          asm volatile("" : "+r"(mx[2*c]), "+r"(mx[2*c+1]) :: "memory"); \
        } \
        fph ^= 0x14u; } while (0)
    PHASE_S(, sh);
    #pragma unroll 1
    for (int h = 0; ; h++) {
      const uint32_t hodd = h & 1;
      const bool last = h == 3, gq = h + sh < 3;
      const uint32_t ma = sb + OFF_MAX + hodd * 576 + (lane & 3) * 144;
      uint32_t l2[18];
      {
        float a0[72];
        #define U0(j) ((j) <= 2 ? 0 : ((j) >= 16 ? 27 : (((j) - 2) * 27) / 14))
        uint32_t mm[2][2], pk[2][4];
        float4 mr;
        uint16_t eh[2][8];
        #define GP(j) ((j) < 0 ? 1 : ((j) < 5 ? (int)((GLAP0 >> (((j) & 7) * 4)) & 15) : 1 + (j) % 5))
        #define GSTEP(j) do { \
          WAITF(GP(j), ((j) / 5) & 1); \
          if ((j) > 0) { wg_wait<0>(); if ((j) < 15) RELX(GP((j) - 1), (j) < 12); } \
          if ((j) != 1) GMEM(j); \
          GMMA(a0, d0w, d0, GP(j) * PAIR, (j) == 0); \
          if ((j) == 1) { mbar_wait(maxbar, hodd); GMEM(j); } \
          if ((j) == 0) { \
            uint32_t r3[3]; warp_col_reduce<true>(mx, r3, lane); \
            const int jb = (lane & 16) ? 9 : 0, j0 = jb + ((lane & 8) ? 4 : 0) + ((lane & 4) ? 2 : 0); \
            red_max_f32(ma + j0 * 8, bf_lo(r3[0]), true);      red_max_f32(ma + j0 * 8 + 4, bf_hi(r3[0]), true); \
            red_max_f32(ma + j0 * 8 + 8, bf_lo(r3[1]), true);  red_max_f32(ma + j0 * 8 + 12, bf_hi(r3[1]), true); \
            red_max_f32(ma + (jb + 8) * 8, bf_lo(r3[2]), !(lane & 12)); red_max_f32(ma + (jb + 8) * 8 + 4, bf_hi(r3[2]), !(lane & 12)); \
            __syncwarp(); if (lane == 0) mbar_arrive(maxbar); } \
          GEXP(j); } while (0)
        #define GMEM(j) do { \
          _Pragma("unroll") for (int u = U0(j); u < U0((j) + 1); u++) if (u % 3 == 0) { \
            mm[(u / 3) & 1][0] = __byte_perm(__float_as_uint(mr.x), __float_as_uint(mr.y), 0x7632); \
            mm[(u / 3) & 1][1] = __byte_perm(__float_as_uint(mr.z), __float_as_uint(mr.w), 0x7632); } \
          _Pragma("unroll") for (int u = U0((j) - 1); u < U0(j); u++) if (u % 3 == 0) { \
            const int c = u / 3; uint16_t (&e)[8] = eh[u - U0((j) - 1)]; \
            const uint32_t k0 = pack_halves(e[0], e[1]), k1 = pack_halves(e[2], e[3]), k2 = pack_halves(e[4], e[5]), k3 = pack_halves(e[6], e[7]); \
            stsm4t(st_base + c * 2048, k0, k1, k2, k3); \
            l2[2*c] = add_bf16x2(k0, k1); l2[2*c+1] = add_bf16x2(k2, k3); asm volatile("" : "+r"(l2[2*c]), "+r"(l2[2*c+1])); } \
          _Pragma("unroll") for (int u = U0((j) + 1); u < U0((j) + 2); u++) if (u % 3 == 0) { \
            const int c = u / 3; \
            mr = lds128(ma + c * 16); \
            ldsm4t(st_base + c * 2048, pk[c & 1][0], pk[c & 1][1], pk[c & 1][2], pk[c & 1][3]); \
          } } while (0)
        #define GEXP(j) do { \
          _Pragma("unroll") for (int u = U0((j) - 1); u < U0(j); u++) if (u % 3) { \
            const int c = u / 3, t = u % 3; uint16_t (&e)[8] = eh[u - U0((j) - 1)]; \
            uint32_t (&q)[36] = sp[t ? t - 1 : 0]; \
            q[4*c] = pack_halves_pin(e[0], e[1]); q[4*c+1] = pack_halves_pin(e[2], e[3]); \
            q[4*c+2] = pack_halves_pin(e[4], e[5]); q[4*c+3] = pack_halves_pin(e[6], e[7]); \
            l2[2*c] = add_bf16x2(l2[2*c], add_bf16x2(q[4*c], q[4*c+1])); l2[2*c+1] = add_bf16x2(l2[2*c+1], add_bf16x2(q[4*c+2], q[4*c+3])); \
            asm volatile("" : "+r"(l2[2*c]), "+r"(l2[2*c+1])); \
          } \
          _Pragma("unroll") for (int u = U0(j); u < U0((j) + 1); u++) { \
            const int c = u / 3, t = u % 3; uint16_t (&e)[8] = eh[u - U0(j)]; \
            const uint32_t* q = t ? &sp[t ? t - 1 : 0][4*c] : pk[c & 1]; \
            ex2_halves(sub_bf16x2(q[0], mm[c & 1][0]), e[0], e[1]); ex2_halves(sub_bf16x2(q[1], mm[c & 1][0]), e[2], e[3]); \
            ex2_halves(sub_bf16x2(q[2], mm[c & 1][1]), e[4], e[5]); ex2_halves(sub_bf16x2(q[3], mm[c & 1][1]), e[6], e[7]); \
            if (t == 1) { \
              sp[2][4*c] = sub_bf16x2(sp[2][4*c], mm[c & 1][0]); sp[2][4*c+1] = sub_bf16x2(sp[2][4*c+1], mm[c & 1][0]); \
              sp[2][4*c+2] = sub_bf16x2(sp[2][4*c+2], mm[c & 1][1]); sp[2][4*c+3] = sub_bf16x2(sp[2][4*c+3], mm[c & 1][1]); \
              asm volatile("" : "+r"(sp[2][4*c]), "+r"(sp[2][4*c+1]), "+r"(sp[2][4*c+2]), "+r"(sp[2][4*c+3])); } \
          } } while (0)
        GSTEP(0); GSTEP(1); GSTEP(2); GSTEP(3); GSTEP(4); GSTEP(5); GSTEP(6); GSTEP(7);
        GSTEP(8); GSTEP(9); GSTEP(10); GSTEP(11); GSTEP(12); GSTEP(13); GSTEP(14); GSTEP(15);
        fph ^= 0x3Cu;
        WAITF(2, 0);
        GMEM(16); GEXP(16);
        fence_async_smem();
        bar_sync<3, 256>();
        wg_wait<0>();
        fence_regs(a0);
        if (w) bar_arrive<10, 256>();
        if (gq) {
          #pragma unroll
          for (int i = 0; i < 72; i++) a0[i] *= cs;
        }
        store_acc_T(a0, st_base + 5 * PAIR);
        if (!gq && !last) STG_ARRIVE();
      }
      float o[72];
      #define STORE_P(i) do { _Pragma("unroll") for (int c_ = 0; c_ < 9; c_++) \
          stsm4t(st_base + ((i) & 1) * PAIR + c_ * 2048, sp[(i)-1][4*c_], sp[(i)-1][4*c_+1], sp[(i)-1][4*c_+2], sp[(i)-1][4*c_+3]); } while (0)
      #define PVSTEP(i) do { \
        constexpr int v_ = (i) == 3 ? 2 : 2 + (i), pb_ = ((i) & 1) * PAIR; \
        if ((i) > 0) { \
          if (!w) { bar_sync<9 + ((i) & 1), 256>(); STORE_P((i) ? (i) : 1); } \
          if ((i) == 3) { \
            uint32_t r3[3]; \
            warp_col_reduce<false>(l2, r3, lane); \
            const int jb = (lane & 16) ? 9 : 0, j0 = jb + ((lane & 8) ? 4 : 0) + ((lane & 4) ? 2 : 0); \
            const uint32_t sa = sb + OFF_SUM + (w * 4 + warp) * 288 + (lane & 3) * 72; \
            sts32(sa + j0 * 4, r3[0]); sts32(sa + j0 * 4 + 4, r3[1]); sts32(sa + (jb + 8) * 4, r3[2]); \
            if (t128 < 72) sts32(sb + OFF_MAX + (hodd ^ 1) * 576 + w * 288 + t128 * 4, 0xff800000u); \
            bar_arrive<4, 288>(); } \
          wg_wait<0>(); \
          RELX(1 + (i), (i) > 1 && last && !(sh && (i) == 2)); \
        } \
        if (w) { \
          if ((i) > 0 && (i) < 3) bar_arrive<10 - ((i) & 1), 256>(); \
          bar_sync<6, 256>(); \
          if ((i) < 3) STORE_P((i) < 3 ? (i) + 1 : 1); \
        } \
        if ((i) > 0) WAITF(v_, (i) == 3); \
        if (w ? (i) < 3 : (i) > 0) fence_async_smem(); \
        if (!w && (i) > 0) bar_sync<5, 256>(); \
        if ((i) > 0) fence_regs(o); \
        wg_fence(); \
        if ((i) == 0) mma_init<1, v_ * PAIR, pb_>(o, d0v, d0); else mma<1, v_ * PAIR, pb_>(o, d0v, d0); \
        mma<1, v_ * PAIR + 2048, pb_ + 32>(o, d0v, d0); mma<1, v_ * PAIR + 4096, pb_ + 64>(o, d0v, d0); mma<1, v_ * PAIR + 6144, pb_ + 96>(o, d0v, d0); \
        mma<1, v_ * PAIR + 8192, pb_ + SLOT>(o, d0v, d0);       mma<1, v_ * PAIR + 10240, pb_ + SLOT + 32>(o, d0v, d0); \
        mma<1, v_ * PAIR + 12288, pb_ + SLOT + 64>(o, d0v, d0); mma<1, v_ * PAIR + 14336, pb_ + SLOT + 96>(o, d0v, d0); \
        wg_commit(); \
        TURN_PASS(); \
        if ((i) < 3) { sched_sep(P.zero); \
            \
          if ((i) < 2) { _Pragma("unroll") for (int r_ = (i) * 18; r_ < (i) * 18 + 18; r_++) { sp[2][r_] = ex2_bf16x2(sp[2][r_]); asm volatile("" : "+r"(sp[2][r_])); } } \
          else { _Pragma("unroll") for (int r_ = 0; r_ < 18; r_++) \
              asm volatile("{\n.reg .b32 t;\nadd.rn.bf16x2 t, %1, %2;\nadd.rn.bf16x2 %0, %0, t;\n}\n" : "+r"(l2[r_]) : "r"(sp[2][2*r_]), "r"(sp[2][2*r_+1])); } \
          sched_sep(P.zero); } } while (0)
      PVSTEP(0);
      PVSTEP(1);
      PVSTEP(2);
      PVSTEP(3);
      fph ^= 0x18u;
      wg_wait<0>();
      fence_regs(o);
      RELX(2, last); REL(1);
      #define LOAD_IV() float4 iv[9]; if (w) bar_sync<8, 160>(); else bar_sync<7, 160>(); \
          _Pragma("unroll") for (int j = 0; j < 9; j++) iv[j] = lds128(sb + OFF_INV + (lane & 3) * 144 + j * 16)
      if (last) {
        LOAD_IV();
        if (!w) bar_sync<5, 256>();
        O_NORM_STSM();
        break;
      }
      if (sh && h == 2) { WAITF(5, 0); fph ^= 0x20u; }
      LOAD_IV();
      PHASE_S(sched_sep(P.zero); O_NORM_STSM(); sched_sep(P.zero), true);
    }
    {
      float a0[72];
      #pragma unroll
      for (int i = 0; i < 72; i++) a0[i] = 0.f;
      const uint32_t dg = (lane >> 3) == (lane & 3) ? ((lane & 4) ? 0x3f800000u : 0x00003f80u) : 0u;
      const uint32_t db = d0 + w * (SLOT / 16);
      const uint32_t g0 = warp == 0 ? dg : 0u, g1 = warp == 1 ? dg : 0u, g2 = warp == 2 ? dg : 0u, g3 = warp == 3 ? dg : 0u;
      #define FOLD(p) do { fence_regs(a0); wg_fence(); \
          mma_rs<(p) * PAIR>(a0, g0, db); mma_rs<(p) * PAIR + 32>(a0, g1, db); mma_rs<(p) * PAIR + 64>(a0, g2, db); mma_rs<(p) * PAIR + 96>(a0, g3, db); \
          wg_commit(); } while (0)
      FOLD(5); STG_ARRIVE(); wg_wait<0>(); fence_regs(a0); REL(5);
      if (sh) { WAITF(3, 0); FOLD(3); wg_wait<0>(); fence_regs(a0); REL(3); fph ^= 0x08u; }
      int sprev = 0;
      XLOOP(a0, 0, 48 - 16 * sh, 1 + sh, true);
      STG_FREE();
      wg_wait<0>();
      fence_regs(a0);
      store_acc_T(a0, st_base);
      STG_ARRIVE();
    }
    cluster_sync();
    #undef lane
    #undef warp
  }
}

typedef CUresult (*PFN_enc)(CUtensorMap*, CUtensorMapDataType, cuuint32_t, void*, const cuuint64_t*, const cuuint64_t*,
                            const cuuint32_t*, const cuuint32_t*, CUtensorMapInterleave, CUtensorMapSwizzle,
                            CUtensorMapL2promotion, CUtensorMapFloatOOBfill);

void enc2d(PFN_enc enc, CUtensorMap* m, const void* p, uint64_t cols, uint64_t rows, uint32_t box_rows) {
  cuuint64_t dims[2] = {cols, rows}; cuuint64_t st[1] = {cols * 2};
  cuuint32_t box[2] = {64, box_rows}; cuuint32_t es[2] = {1, 1};
  enc(m, CU_TENSOR_MAP_DATA_TYPE_BFLOAT16, 2, (void*)p, dims, st, box, es, CU_TENSOR_MAP_INTERLEAVE_NONE,
      CU_TENSOR_MAP_SWIZZLE_128B, CU_TENSOR_MAP_L2_PROMOTION_L2_128B, CU_TENSOR_MAP_FLOAT_OOB_FILL_NONE);
}
void enc3d(PFN_enc enc, CUtensorMap* m, const void* p, uint64_t cols, uint64_t rows, uint32_t box_rows) {
  cuuint64_t dims[3] = {64, rows, cols / 64}; cuuint64_t st[2] = {cols * 2, 128};
  cuuint32_t box[3] = {64, box_rows, 2}; cuuint32_t es[3] = {1, 1, 1};
  enc(m, CU_TENSOR_MAP_DATA_TYPE_BFLOAT16, 3, (void*)p, dims, st, box, es, CU_TENSOR_MAP_INTERLEAVE_NONE,
      CU_TENSOR_MAP_SWIZZLE_128B, CU_TENSOR_MAP_L2_PROMOTION_L2_256B, CU_TENSOR_MAP_FLOAT_OOB_FILL_NONE);
}

}

extern "C" void kernel_launch(void* const* d_in, const int* in_sizes, int n_in, void* d_out, int out_size) {
  (void)in_sizes; (void)n_in; (void)out_size;
  void* fn = nullptr; cudaDriverEntryPointQueryResult q;
  cudaGetDriverEntryPoint("cuTensorMapEncodeTiled", &fn, cudaEnableDefault, &q);
  PFN_enc enc = (PFN_enc)fn;
  void* oscr = nullptr; cudaGetSymbolAddress(&oscr, g_oscr);
  Params P;
  for (int i = 0; i < 2; i++) {
    enc2d(enc, &P.x[i], d_in[5*i + 0], 1024, TOK, 72);
    enc3d(enc, &P.k[i], d_in[5*i + 1], 128, 8 * 32 * 512, 128);
    enc3d(enc, &P.v[i], d_in[5*i + 2], 128, 8 * 32 * 512, 128);
    enc3d(enc, &P.wq[i], d_in[5*i + 3], 4096, 1024, 64);
    enc3d(enc, &P.wo[i], d_in[5*i + 4], 1024, 4096, 64);
    P.kptr[i] = (const char*)d_in[5*i + 1];
  }
  enc2d(enc, &P.os, oscr, 4096, 2 * TOK, 72);
  enc2d(enc, &P.oss, oscr, 4096, 2 * TOK, 24);
  enc2d(enc, &P.out, d_out, 2048, TOK, SQ);
  P.zero = 0;
  cudaFuncSetAttribute(fused_kernel, cudaFuncAttributeMaxDynamicSharedMemorySize, SMEM_BYTES);
  cudaLaunchConfig_t cfg = {};
  cfg.gridDim = dim3(NCTA); cfg.blockDim = dim3(384); cfg.dynamicSmemBytes = SMEM_BYTES; cfg.stream = cudaStreamPerThread;
  cudaLaunchAttribute at[1];
  at[0].id = cudaLaunchAttributeClusterDimension; at[0].val.clusterDim.x = 2; at[0].val.clusterDim.y = 1; at[0].val.clusterDim.z = 1;
  cfg.attrs = at; cfg.numAttrs = 1;
  cudaLaunchKernelEx(&cfg, fused_kernel, P);
}
```
